```python
import torch

def _softmax(x, axis=-1):
    return torch.softmax(x, dim=axis)
def _gelu(x):
    return torch.nn.functional.gelu(x, approximate="tanh")
def _silu(x):
    return torch.nn.functional.silu(x)
def _sigmoid(x):
    return torch.sigmoid(x)
def _layernorm(x, axis=-1, eps=1e-5):
    m = x.mean(dim=axis, keepdim=True)
    v = x.var(dim=axis, keepdim=True, unbiased=False)
    return (x - m) / torch.sqrt(v + eps)
def _scatter_add(tgt, idx, src, axis=0):
    return tgt.clone().index_add_(axis, idx, src)
def _segment_sum(src, seg, n):
    out = torch.zeros((n,) + src.shape[1:], dtype=src.dtype)
    return out.index_add_(0, seg, src)
def _pad(x, pw):
    flat = tuple(v for pair in reversed(pw) for v in pair)
    return torch.nn.functional.pad(x, flat)

kernel_name = 'standalone__edge_featured_mpnn_mpnn__graph'

def setup_inputs():

    _w = (lambda a: (lambda t: t.to(torch.bfloat16) if t.is_floating_point() else t)(torch.as_tensor(a)))
    N, deg, D, De = 10000, 16, 128, max(0, 1)
    E = N * deg
    H = 2 * D
    return {
        "x": _w((lambda *s: torch.randn(*s, dtype=torch.bfloat16) * 0.05)(N, D)),
        "e_attr": _w((lambda *s: torch.randn(*s, dtype=torch.bfloat16) * 1.6)(E, De)),
        "src": _w((lambda lo, hi, *s: torch.randint(lo, hi, s))(0, N, E).to(torch.int64)),
        "dst": _w((lambda lo, hi, *s: torch.randint(lo, hi, s))(0, N, E).to(torch.int64)),
        "w1": _w((lambda *s: torch.randn(*s, dtype=torch.bfloat16) * 1.6)(2 * D + De, H) * (1.0 / (2 * D + De) ** 0.5)),
        "b1": _w((lambda *s: torch.randn(*s, dtype=torch.bfloat16) * 1.6)(H) * 0.01),
        "w2": _w((lambda *s: torch.randn(*s, dtype=torch.bfloat16) * 0.05)(H, D) * (1.0 / H ** 0.5)),
        "b2": _w((lambda *s: torch.randn(*s, dtype=torch.bfloat16) * 0.05)(D) * 0.01),
    }

def reference(x, e_attr, src, dst, w1, b1, w2, b2):
    N, D = x.shape
    h_src = x[src]
    h_dst = x[dst]
    m_in = torch.concatenate([h_src, h_dst, e_attr], axis=-1)
    h = _silu(m_in @ w1 + b1)
    msg = h @ w2 + b2
    return _segment_sum(msg, dst, N)
```

```cpp
#include <cuda_runtime.h>
#include <cuda_bf16.h>
#include <cuda.h>
#include <stdint.h>

#define PFENCE 0
#define PD 2
#define REP 1
#define POLL "ld.relaxed.gpu.global.u32"
#define SYNC_LESS 4
#define LDMODE "ld.global.L1::no_allocate.v4.u32"
#define VAR 7

namespace {

constexpr int kNT = 80;
constexpr int kThreads = 896;
constexpr int kWarps = kThreads / 32;
constexpr int kBinThreads = 352;
constexpr int kSyncWarp = 11;
constexpr int kMaxN = 16384;
constexpr int kMaxG = 132;
constexpr int kCell = 32;
constexpr int kCellB = 160;
constexpr int kMaxE = 262144;

constexpr int OFF_W1A = 0;
constexpr int OFF_X = 65536;
constexpr int OFF_W2 = 86016;
constexpr int OFF_W1B = 151552;
constexpr int OFF_IMG = OFF_W2;
constexpr int OFF_PST = OFF_W2 + 21504;
constexpr int OFF_MISC = OFF_W1B + 65536;
constexpr int OFF_HS = 0;
constexpr int OFF_REC = 40960;
constexpr int OFF_SIDE = OFF_REC + kMaxG * kCell * 4 - 1024;
constexpr int OFF_BAR = OFF_MISC;
constexpr int OFF_EN = OFF_MISC + 128;
constexpr int OFF_NCNT = OFF_EN + 96 * 4;
constexpr int OFF_RDY = OFF_NCNT + 128 * 4;
constexpr int OFF_FLAG = OFF_RDY + 32 * 4;
constexpr int OFF_OCNT = OFF_FLAG + 32;
constexpr int OFF_B2 = OFF_OCNT + 168 * 4;
constexpr int OFF_W1C = OFF_B2 + 512;
constexpr int OFF_PAR = OFF_W1C + 512;
constexpr int OFF_DUMMY = OFF_PAR + 16;
constexpr int OFF_PROF = OFF_DUMMY + 128;
constexpr int kSmemBytes = OFF_PROF + 256 + 1024;
static_assert(kSmemBytes <= 232448, "smem");
static_assert(kMaxG * 4 <= kThreads - 32, "mailbox mapping");
static_assert(OFF_SIDE + kWarps * 1024 <= OFF_W2, "side rows");
static_assert(OFF_EN % 16 == 0 && OFF_NCNT % 16 == 0 && OFF_B2 % 16 == 0 && OFF_W1C % 16 == 0, "align");

__device__ uint4 g_P[2 * kMaxN * 32];
__device__ uint4 g_mbox[kMaxG * kMaxG * kCellB / 16];
__device__ uint2 g_ovf[kMaxE];
__device__ int g_ovf_cnt[kMaxG];
constexpr int kRep = REP, kRepStride = 64;
__device__ unsigned int g_bar[2 * kRep * kRepStride];
#define GSTAMP(i)
#define STAMP(i)

__device__ __forceinline__ uint32_t prmt(uint32_t a, uint32_t b, uint32_t s) {
  uint32_t d;
  asm("prmt.b32 %0,%1,%2,%3;" : "=r"(d) : "r"(a), "r"(b), "r"(s));
  return d;
}
__device__ __forceinline__ uint32_t hfma2(uint32_t a, uint32_t b, uint32_t c) {
  uint32_t d;
  asm("fma.rn.bf16x2 %0,%1,%2,%3;" : "=r"(d) : "r"(a), "r"(b), "r"(c));
  return d;
}
__device__ __forceinline__ uint32_t hadd2(uint32_t a, uint32_t b) {
  uint32_t d;
  asm("add.rn.bf16x2 %0,%1,%2;" : "=r"(d) : "r"(a), "r"(b));
  return d;
}
__device__ __forceinline__ uint32_t htanh2(uint32_t a) {
  uint32_t d;
  asm("tanh.approx.bf16x2 %0,%1;" : "=r"(d) : "r"(a));
  return d;
}
__device__ __forceinline__ float ftanh(float x) {
  float y;
  asm("tanh.approx.f32 %0,%1;" : "=f"(y) : "f"(x));
  return y;
}
__device__ __forceinline__ uint32_t pack2(float lo, float hi) {
  uint32_t d;
  asm("cvt.rn.bf16x2.f32 %0,%1,%2;" : "=r"(d) : "f"(hi), "f"(lo));
  return d;
}
__device__ __forceinline__ float lo_f(uint32_t v) { return __uint_as_float(prmt(v, 0, 0x1044)); }
__device__ __forceinline__ float hi_f(uint32_t v) { return __uint_as_float(v & 0xffff0000u); }

__device__ __forceinline__ void mbar_init(uint32_t bar, uint32_t cnt) {
  asm volatile("mbarrier.init.shared::cta.b64 [%0], %1;" ::"r"(bar), "r"(cnt) : "memory");
}
__device__ __forceinline__ void mbar_expect(uint32_t bar, uint32_t bytes) {
  asm volatile("mbarrier.arrive.expect_tx.shared::cta.b64 _, [%0], %1;" ::"r"(bar), "r"(bytes) : "memory");
}
__device__ __forceinline__ void mbar_wait(uint32_t bar, uint32_t parity) {
  uint32_t ok = 0;
#pragma unroll 1
  for (int it = 0; it < (1 << 22) && !ok; ++it) {
    asm volatile(
        "{.reg .pred p; mbarrier.try_wait.parity.shared::cta.b64 p, [%1], %2, %3; selp.u32 %0, 1, 0, p;}"
        : "=r"(ok)
        : "r"(bar), "r"(parity), "r"(20000u)
        : "memory");
  }
}
__device__ __forceinline__ void tma2d(uint32_t dst, const CUtensorMap* m, int c0, int c1, uint32_t bar) {
  asm volatile(
      "cp.async.bulk.tensor.2d.shared::cluster.global.mbarrier::complete_tx::bytes [%0], [%1, {%2, %3}], [%4];" ::"r"(dst),
      "l"(m), "r"(c0), "r"(c1), "r"(bar)
      : "memory");
}
__device__ __forceinline__ void bar_sync(int id, int n) { asm volatile("bar.sync %0, %1;" ::"r"(id), "r"(n) : "memory"); }
__device__ __forceinline__ void bar_arrive(int id, int n) {
  asm volatile("bar.arrive %0, %1;" ::"r"(id), "r"(n) : "memory");
}
__device__ __forceinline__ bool bar_or(int id, int n, bool v) {
  uint32_t r;
  asm volatile("{.reg .pred p, q; setp.ne.u32 p, %3, 0; bar.red.or.pred q, %1, %2, p; selp.u32 %0, 1, 0, q;}"
               : "=r"(r)
               : "r"(id), "r"(n), "r"((uint32_t)v)
               : "memory");
  return r != 0;
}
__device__ __forceinline__ uint32_t desc_lo(uint32_t addr) { return ((addr & 0x3FFFF) >> 4) | (1u << 16); }
__device__ __forceinline__ uint64_t mk_desc(uint32_t lo) {
  return (uint64_t)lo | ((64ull | (1ull << 30)) << 32);
}
__device__ __forceinline__ uint32_t atoms_inc(uint32_t a) {
  uint32_t r;
  asm volatile("atom.shared.add.u32 %0, [%1], 1;" : "=r"(r) : "r"(a) : "memory");
  return r;
}

__device__ __forceinline__ void wgmma_n80(float (&d)[40], uint64_t da, uint64_t db, int acc) {
  asm volatile(
      "{.reg .pred p; setp.ne.b32 p, %42, 0;\n"
      "wgmma.mma_async.sync.aligned.m64n80k16.f32.bf16.bf16 "
      "{%0,%1,%2,%3,%4,%5,%6,%7,%8,%9,%10,%11,%12,%13,%14,%15,%16,%17,%18,%19,"
      "%20,%21,%22,%23,%24,%25,%26,%27,%28,%29,%30,%31,%32,%33,%34,%35,%36,%37,%38,%39},"
      "%40, %41, p, 1, 1, 1, 0;}\n"
      : "+f"(d[0]), "+f"(d[1]), "+f"(d[2]), "+f"(d[3]), "+f"(d[4]), "+f"(d[5]), "+f"(d[6]), "+f"(d[7]), "+f"(d[8]),
        "+f"(d[9]), "+f"(d[10]), "+f"(d[11]), "+f"(d[12]), "+f"(d[13]), "+f"(d[14]), "+f"(d[15]), "+f"(d[16]),
        "+f"(d[17]), "+f"(d[18]), "+f"(d[19]), "+f"(d[20]), "+f"(d[21]), "+f"(d[22]), "+f"(d[23]), "+f"(d[24]),
        "+f"(d[25]), "+f"(d[26]), "+f"(d[27]), "+f"(d[28]), "+f"(d[29]), "+f"(d[30]), "+f"(d[31]), "+f"(d[32]),
        "+f"(d[33]), "+f"(d[34]), "+f"(d[35]), "+f"(d[36]), "+f"(d[37]), "+f"(d[38]), "+f"(d[39])
      : "l"(da), "l"(db), "r"(acc)
      : "memory");
}
__device__ __forceinline__ void wg_fence() { asm volatile("wgmma.fence.sync.aligned;" ::: "memory"); }
__device__ __forceinline__ void wg_commit() { asm volatile("wgmma.commit_group.sync.aligned;" ::: "memory"); }
__device__ __forceinline__ void wg_wait() { asm volatile("wgmma.wait_group.sync.aligned 0;" ::: "memory"); }

__device__ __forceinline__ uint4 lds128(uint32_t a) {
  uint4 v;
  asm volatile("ld.shared.v4.u32 {%0,%1,%2,%3}, [%4];" : "=r"(v.x), "=r"(v.y), "=r"(v.z), "=r"(v.w) : "r"(a));
  return v;
}
__device__ __forceinline__ uint2 lds64(uint32_t a) {
  uint2 v;
  asm volatile("ld.shared.v2.u32 {%0,%1}, [%2];" : "=r"(v.x), "=r"(v.y) : "r"(a));
  return v;
}
__device__ __forceinline__ uint32_t lds32(uint32_t a) {
  uint32_t v;
  asm volatile("ld.shared.u32 %0, [%1];" : "=r"(v) : "r"(a));
  return v;
}
__device__ __forceinline__ void sts128(uint32_t a, uint4 v) {
  asm volatile("st.shared.v4.u32 [%0], {%1,%2,%3,%4};" ::"r"(a), "r"(v.x), "r"(v.y), "r"(v.z), "r"(v.w) : "memory");
}
__device__ __forceinline__ void sts64(uint32_t a, uint32_t x, uint32_t y) {
  asm volatile("st.shared.v2.u32 [%0], {%1,%2};" ::"r"(a), "r"(x), "r"(y) : "memory");
}
__device__ __forceinline__ void sts32(uint32_t a, uint32_t x) {
  asm volatile("st.shared.u32 [%0], %1;" ::"r"(a), "r"(x) : "memory");
}
__device__ __forceinline__ void ldrow(uint4& v, uint32_t plo, uint32_t phi, uint32_t r, bool pred) {
  asm volatile(
      "{.reg .pred p; .reg .b64 a; setp.ne.b32 p, %6, 0; mov.b64 a, {%4, %5};\n"
      "@p " LDMODE " {%0,%1,%2,%3}, [a];}"
      : "+r"(v.x), "+r"(v.y), "+r"(v.z), "+r"(v.w)
      : "r"(prmt(r, 0, 0x4104) + plo), "r"(phi), "r"((int)pred));
}

__device__ __forceinline__ void store_hsum(uint32_t sb, int node, int lane, const float (&a)[8]) {
  uint32_t ad = sb + OFF_HS + (lane >> 3) * 10240 + node * 128 + (((lane & 6) ^ (node & 7)) << 4) + ((lane & 1) << 3);
  sts64(ad, pack2(a[0], a[2]), pack2(a[4], a[6]));
  sts64(ad ^ 16, pack2(a[1], a[3]), pack2(a[5], a[7]));
}

__device__ __forceinline__ void store_side(uint32_t sb, int warp, int lane, const float (&a)[8]) {
  const uint32_t ad = sb + OFF_SIDE + warp * 1024 + lane * 16;
  sts128(ad, make_uint4(__float_as_uint(a[0]), __float_as_uint(a[1]), __float_as_uint(a[2]), __float_as_uint(a[3])));
  sts128(ad + 512, make_uint4(__float_as_uint(a[4]), __float_as_uint(a[5]), __float_as_uint(a[6]), __float_as_uint(a[7])));
  __syncwarp();
  asm volatile("st.release.cta.shared.u32 [%0], 1;" ::"r"(sb + OFF_RDY + warp * 4) : "memory");
}
__device__ __forceinline__ int range_start(int T, int w) {
  const int d = min(SYNC_LESS, (T / kWarps) & ~1);
  return w >= kWarps ? T : 2 * (((T + d) * w + kWarps) / (2 * kWarps)) - (w > kSyncWarp ? d : 0);
}

__global__ void __launch_bounds__(kThreads, 1)
mpnn_kernel(const int* __restrict__ dst, const int* __restrict__ src, const uint16_t* __restrict__ e_attr, int E,
            int epc, int N, int npc, uint32_t npc_magic, const uint16_t* __restrict__ w1,
            const uint16_t* __restrict__ w2, const uint16_t* __restrict__ b1, const uint16_t* __restrict__ b2, uint64_t pbase,
            const __grid_constant__ CUtensorMap tmX, const __grid_constant__ CUtensorMap tmW1,
            const __grid_constant__ CUtensorMap tmW2, const __grid_constant__ CUtensorMap tmP,
            const __grid_constant__ CUtensorMap tmM, const __grid_constant__ CUtensorMap tmO) {
  extern __shared__ uint8_t smem_raw[];
  const int tid = threadIdx.x, b = blockIdx.x;
  const int e0 = b * epc, e1 = min(E, e0 + epc);
  int4 dv = make_int4(-1, -1, -1, -1), sv = make_int4(0, 0, 0, 0);
  uint2 ev = make_uint2(0, 0);
  if (tid < kBinThreads && e0 + 4 * tid + 3 < e1) {
    dv = *reinterpret_cast<const int4*>(dst + e0 + 4 * tid);
    sv = *reinterpret_cast<const int4*>(src + e0 + 4 * tid);
    ev = *reinterpret_cast<const uint2*>(e_attr + e0 + 4 * tid);
  }
  const int n0 = b * npc, nn = max(0, min(npc, N - n0));
  uint32_t par = 0;
  const uint32_t sraw = (uint32_t)__cvta_generic_to_shared(smem_raw);
  const uint32_t sb = (sraw + 1023u) & ~1023u;
  const uint8_t* const sp = smem_raw + (sb - sraw);
  const int lane = tid & 31;
  const int warp = __shfl_sync(0xffffffffu, tid >> 5, 0);
  const int wg = warp >> 2, wi = warp & 3;
  const int G = gridDim.x;
  const uint32_t barX = sb + OFF_BAR, barW2 = barX + 8, barM = barX + 80, barR = barX + 88;
  const int g = lane >> 2, t = lane & 3;

  if (warp == kSyncWarp) {
    if (lane == 0) {
      mbar_init(barX, 1);
      mbar_init(barW2, 1);
      mbar_init(barM, 1);
      mbar_init(barR, kWarps - 1);
      asm volatile("fence.mbarrier_init.release.cluster;" ::: "memory");
      mbar_expect(barX, 2 * kNT * 128);
      tma2d(sb + OFF_X, &tmX, 0, n0, barX);
      tma2d(sb + OFF_X + kNT * 128, &tmX, 64, n0, barX);
      mbar_expect(barW2, 65536);
      mbar_expect(barM, G * kCellB);
      STAMP(27);
    }
    __syncwarp();
    uint32_t v0;
    asm volatile("ld.relaxed.gpu.global.u32 %0, [%1];" : "=r"(v0) : "l"(g_bar + (lane % (2 * kRep)) * kRepStride) : "memory");
    const uint2 bb = *reinterpret_cast<const uint2*>(b2 + lane * 4);
    const uint4 w1c = *reinterpret_cast<const uint4*>(w1 + 256 * 256 + lane * 8);
    if (lane == 0) {
      if (b < 128) {
        const uint16_t* pf = b < 64 ? w1 + 128 * 256 + b * 512 : w2 + (b - 64) * 512;
        asm volatile("cp.async.bulk.prefetch.L2.global [%0], 1024;" ::"l"(pf) : "memory");
      }
      asm volatile("prefetch.tensormap [%0];" ::"l"(&tmM) : "memory");
      asm volatile("prefetch.tensormap [%0];" ::"l"(&tmP) : "memory");
      asm volatile("prefetch.tensormap [%0];" ::"l"(&tmW2) : "memory");
      asm volatile("prefetch.tensormap [%0];" ::"l"(&tmO) : "memory");
    }
    bar_sync(13, 512 + 32);
    bar_sync(1, kBinThreads + 32);
    if (lane == 0) {
      asm volatile("cp.async.bulk.tensor.3d.global.shared::cta.bulk_group [%0, {0, %1, 0}], [%2];" ::"l"(&tmM), "r"(b),
                   "r"(sb + OFF_IMG)
                   : "memory");
      asm volatile("cp.async.bulk.commit_group;" ::: "memory");
      STAMP(14);
    }
    __syncwarp();
    if (lane < 4) tma2d(sb + OFF_W1B + lane * 16384, &tmW1, lane * 64, 128, barX + 24 + lane * 16);
    __syncwarp();
    sts128(sb + OFF_B2 + lane * 16, make_uint4(bb.x << 16, bb.x & 0xffff0000u, bb.y << 16, bb.y & 0xffff0000u));
    sts128(sb + OFF_W1C + lane * 16, w1c);
    sts32(sb + OFF_RDY + lane * 4, 0);
    par = v0 < (uint32_t)G ? 1u : 0u;
    sts32(sb + OFF_PAR, par);
    bar_arrive(14, 512 + 32);
    if (lane == 0) {
      asm volatile("cp.async.bulk.wait_group 0;" ::: "memory");
      STAMP(1);
    }
    __syncwarp();
    if (lane < kRep)
      asm volatile("red.relaxed.gpu.global.inc.u32 [%0], %1;" ::"l"(g_bar + lane * kRepStride), "r"(2 * G - 1) : "memory");
    if (lane == 0) {
      uint32_t v;
      int it = 0;
      do {
        asm volatile(POLL " %0, [%1];" : "=r"(v) : "l"(g_bar + (b % kRep) * kRepStride) : "memory");
      } while (((v < (uint32_t)G) == (par != 0)) && ++it < (1 << 22));
      STAMP(12);
      asm volatile("cp.async.bulk.shared::cluster.global.mbarrier::complete_tx::bytes [%0], [%1], %2, [%3];" ::"r"(
                       sb + OFF_IMG),
                   "l"(reinterpret_cast<const uint8_t*>(g_mbox) + (size_t)b * kMaxG * kCellB), "r"(G * kCellB), "r"(barM)
                   : "memory");
    }
    __syncwarp();
    bar_sync(9, 512 + 32);
    if (lane < 4) {
      asm volatile("cp.async.bulk.tensor.2d.global.shared::cta.bulk_group [%0, {%1, %2}], [%3];" ::"l"(&tmP),
                   "r"(lane * 64), "r"(n0), "r"(sb + OFF_PST + lane * 10240)
                   : "memory");
      asm volatile("cp.async.bulk.commit_group;" ::: "memory");
      STAMP(33);
    }
    __syncwarp();
    asm volatile("cp.async.bulk.wait_group 0;" ::: "memory");
    __syncwarp();
    if (lane == 0) {
      STAMP(37);
    }
    __syncwarp();
    if (lane < kRep)
      asm volatile("red.relaxed.gpu.global.inc.u32 [%0], %1;" ::"l"(g_bar + (kRep + lane) * kRepStride), "r"(2 * G - 1)
                   : "memory");
    if (lane == 0) {
      uint32_t v;
      int it = 0;
      do {
        asm volatile(POLL " %0, [%1];" : "=r"(v) : "l"(g_bar + (kRep + b % kRep) * kRepStride) : "memory");
      } while (((v < (uint32_t)G) == (par != 0)) && ++it < (1 << 22));
      STAMP(5);
    }
    __syncwarp();
  } else if (warp < kSyncWarp) {
    const int bt = tid;
    if (bt < 34) sts128(sb + OFF_OCNT + bt * 16, make_uint4(0, 0, 0, 0));
    else if (bt < 58) sts128(sb + OFF_NCNT + (bt - 34) * 16, make_uint4(0, 0, 0, 0));
    else if (bt < 60) sts128(sb + OFF_FLAG + (bt - 58) * 16, make_uint4(0, 0, 0, 0));
    else if (bt == 60) sts32(sb + OFF_EN - 4, 0);
    if (bt < 2 * kMaxG)
      sts128(sb + OFF_IMG + (bt >> 1) * kCellB + 128 + (bt & 1) * 16,
             make_uint4(0x7f7f7f7fu, 0x7f7f7f7fu, 0x7f7f7f7fu, 0x7f7f7f7fu));
    bar_sync(12, kBinThreads);
    bool spilled = false;
    for (int e = e0 + 4 * bt;;) {
      if (e < e1 && e + 3 >= e1) {
        dv.x = dst[e]; sv.x = src[e]; ev.x = e_attr[e];
        if (e + 1 < e1) { dv.y = dst[e + 1]; sv.y = src[e + 1]; ev.x |= (uint32_t)e_attr[e + 1] << 16; }
        if (e + 2 < e1) { dv.z = dst[e + 2]; sv.z = src[e + 2]; ev.y = e_attr[e + 2]; }
      }
      if (bt == 0 && dv.x != -5) STAMP(7);
      const int d4[4] = {dv.x, dv.y, dv.z, dv.w};
      const uint32_t r4[4] = {prmt(2 * sv.x, ev.x, 0x5410), prmt(2 * sv.y, ev.x, 0x7610), prmt(2 * sv.z, ev.y, 0x5410),
                              prmt(2 * sv.w, ev.y, 0x7610)};
      uint32_t ow[4], pos[4];
#pragma unroll
      for (int i = 0; i < 4; ++i) {
        ow[i] = d4[i] >= 0 ? __umulhi((uint32_t)d4[i], npc_magic) : 136 + lane;
        pos[i] = atoms_inc(sb + OFF_OCNT + ow[i] * 4);
      }
      bool over = false;
#pragma unroll
      for (int i = 0; i < 4; ++i) {
        const bool ok = d4[i] >= 0 && pos[i] < kCell;
        over |= d4[i] >= 0 && pos[i] >= kCell;
        const uint32_t cell = sb + OFF_IMG + ow[i] * kCellB;
        sts32(ok ? cell + pos[i] * 4 : sb + OFF_DUMMY + lane * 4, r4[i]);
        asm volatile("st.shared.u8 [%0], %1;" ::"r"(ok ? cell + 128 + pos[i] : sb + OFF_DUMMY + lane * 4),
                     "r"(d4[i] - ow[i] * npc)
                     : "memory");
      }
      if (over) {
        spilled = true;
#pragma unroll 1
        for (int i = 0; i < 4; ++i) {
          const uint32_t ps = i == 0 ? pos[0] : i == 1 ? pos[1] : i == 2 ? pos[2] : pos[3];
          const int dd = i == 0 ? d4[0] : i == 1 ? d4[1] : i == 2 ? d4[2] : d4[3];
          if (dd >= 0 && ps >= kCell)
            g_ovf[e0 + atoms_inc(sb + OFF_FLAG + 20)] =
                make_uint2((uint32_t)dd, i == 0 ? r4[0] : i == 1 ? r4[1] : i == 2 ? r4[2] : r4[3]);
        }
      }
      e += 4 * kBinThreads;
      if (e - 4 * bt >= e1) break;
      dv = make_int4(-1, -1, -1, -1);
      if (e + 3 < e1) {
        dv = *reinterpret_cast<const int4*>(dst + e);
        sv = *reinterpret_cast<const int4*>(src + e);
        ev = *reinterpret_cast<const uint2*>(e_attr + e);
      }
    }
    if (bar_or(12, kBinThreads, spilled)) {
      if (bt == 0) g_ovf_cnt[b] = (int)lds32(sb + OFF_FLAG + 20);
      if (bt < G && lds32(sb + OFF_OCNT + bt * 4) > kCell)
        sts32(sb + OFF_IMG + bt * kCellB, lds32(sb + OFF_IMG + bt * kCellB) | (1u << 15));
      __threadfence();
      asm volatile("fence.proxy.async;" ::: "memory");
    }
    asm volatile("fence.proxy.async.shared::cta;" ::: "memory");
    bar_sync(1, kBinThreads + 32);
    if (bt == 0) STAMP(15);
  } else {
    const int m = wg - 3;
    const uint32_t barA = barX + 16 + m * 16, barB = barA + 8;
    const uint32_t sa = sb + OFF_W1A + m * 16384, sq = sb + OFF_W1B + m * 16384;
    if ((tid & 127) == 0) {
      mbar_init(barA, 1);
      mbar_init(barB, 1);
      asm volatile("fence.mbarrier_init.release.cluster;" ::: "memory");
      mbar_expect(barA, 16384);
      tma2d(sa, &tmW1, m * 64, 0, barA);
      mbar_expect(barB, 16384);
    }
    __syncwarp();
    const float bl = 0.5f * __uint_as_float((uint32_t)b1[64 * m + 16 * wi + g] << 16);
    const float bh = 0.5f * __uint_as_float((uint32_t)b1[64 * m + 16 * wi + g + 8] << 16);
    bar_sync(13, 512 + 32);
    const uint32_t so = 2 * t * 128 + (((2 * wi + (g >> 2)) ^ (2 * t)) << 4) + (g & 3) * 4;
    const uint32_t dx = desc_lo(sb + OFF_X);
    float acc[40];
    mbar_wait(barA, 0);
    mbar_wait(barX, 0);
    if (tid == 384) STAMP(2);
    wg_fence();
#pragma unroll
    for (int k = 0; k < 8; ++k)
      wgmma_n80(acc, mk_desc(desc_lo(sa) + k * 128), mk_desc(dx + (k >> 2) * (kNT * 8) + (k & 3) * 2), k);
    wg_commit();
    bar_sync(14, 512 + 32);
    par = lds32(sb + OFF_PAR);
    wg_wait();
    if (tid == 384) STAMP(3);
    const uint32_t keep = (g & 3) == 0 ? 0xfffffffeu : 0xffffffffu, tag = par & ~keep;
    const uint32_t ps = sb + OFF_PST + m * 10240;
#pragma unroll
    for (int j = 0; j < 10; ++j) {
      sts32(ps + j * 1024 + so, (hfma2(pack2(acc[4 * j], acc[4 * j + 2]), 0x3f003f00u, 0x80008000u) & keep) | tag);
      sts32(ps + j * 1024 + 128 + (so ^ 16), (hfma2(pack2(acc[4 * j + 1], acc[4 * j + 3]), 0x3f003f00u, 0x80008000u) & keep) | tag);
    }
    asm volatile("fence.proxy.async.shared::cta;" ::: "memory");
    bar_arrive(9, 512 + 32);
    if (tid == 384) STAMP(34);
    mbar_wait(barB, 0);
    wg_fence();
#pragma unroll
    for (int k = 0; k < 8; ++k)
      wgmma_n80(acc, mk_desc(desc_lo(sq) + k * 128), mk_desc(dx + (k >> 2) * (kNT * 8) + (k & 3) * 2), k);
    wg_commit();
    wg_wait();
    bar_sync(2 + m, 128);
#pragma unroll
    for (int j = 0; j < 10; ++j) {
      sts32(sq + j * 1024 + so, pack2(fmaf(acc[4 * j], 0.5f, bl), fmaf(acc[4 * j + 2], 0.5f, bh)));
      sts32(sq + j * 1024 + 128 + (so ^ 16), pack2(fmaf(acc[4 * j + 1], 0.5f, bl), fmaf(acc[4 * j + 3], 0.5f, bh)));
    }
    if (tid == 384) STAMP(11);
  }
  const uint32_t qbase = sb + OFF_W1B + (lane >> 3) * 16384;
  const uint32_t plo = (uint32_t)pbase + lane * 16, phi = (uint32_t)(pbase >> 32);

  uint4 en4;
  if (warp != kSyncWarp) {
    const int wt = warp < kSyncWarp ? tid : tid - 32;
    const bool has = wt < 4 * G;
    const uint32_t cp = sb + OFF_IMG + (wt >> 2) * kCellB + (wt & 3) * 4;
    uint4 mw[2];
    uint32_t md[2] = {0x7f7f7f7fu, 0x7f7f7f7fu}, rk[8];
    mbar_wait(barM, 0);
    if (has) {
      md[0] = lds32(cp + 128);
      md[1] = lds32(cp + 144);
      mw[0] = lds128(cp + (wt & 3) * 12);
    }
    if (tid == 0 && md[0] != 5) STAMP(16);
    const bool any0 = __any_sync(0xffffffffu, has), any1 = __any_sync(0xffffffffu, md[1] != 0x7f7f7f7fu);
    if (any0) {
#pragma unroll
      for (int i = 0; i < 4; ++i) {
        const uint32_t id = (md[0] >> (8 * i)) & 0x7fu;
        rk[i] = atoms_inc(sb + OFF_NCNT + (id != 0x7fu ? id : 96 + lane) * 4);
      }
    }
    if (any1) {
      mw[1] = lds128(cp + (wt & 3) * 12 + 64);
#pragma unroll
      for (int i = 0; i < 4; ++i) {
        const uint32_t id = (md[1] >> (8 * i)) & 0x7fu;
        rk[4 + i] = atoms_inc(sb + OFF_NCNT + (id != 0x7fu ? id : 96 + lane) * 4);
      }
      if ((wt & 3) == 0 && md[1] != 0x7f7f7f7fu && (mw[0].x & (1u << 15)))
        asm volatile("red.shared.or.b32 [%0], %1;" ::"r"(sb + OFF_FLAG + (wt >> 7) * 4), "r"(1u << ((wt >> 2) & 31))
                     : "memory");
    }
    bar_sync(11, kThreads - 32);
    const uint4 c4 = lane < 24 ? lds128(sb + OFF_NCNT + lane * 16) : make_uint4(0, 0, 0, 0);
    {
      const uint32_t tot = c4.x + c4.y + c4.z + c4.w;
      uint32_t v = tot;
#pragma unroll
      for (int o = 1; o < 32; o <<= 1) {
        const uint32_t u = __shfl_up_sync(0xffffffffu, v, o);
        if (lane >= o) v += u;
      }
      en4 = make_uint4(v - tot + c4.x, v - c4.z - c4.w, v - c4.w, v);
      if (lane < 24) sts128(sb + OFF_EN + lane * 16, en4);
      __syncwarp();
    }
    if (tid == 0) STAMP(17);
#pragma unroll
    for (int k = 0; k < 2; ++k) {
      if (k == 0 ? any0 : any1) {
        uint32_t st[4];
#pragma unroll
        for (int i = 0; i < 4; ++i) st[i] = lds32(sb + OFF_EN - 4 + ((md[k] >> (8 * i)) & 0x7fu) * 4);
        const uint32_t w4[4] = {mw[k].x, mw[k].y, mw[k].z, mw[k].w};
#pragma unroll
        for (int i = 0; i < 4; ++i) {
          const uint32_t id = (md[k] >> (8 * i)) & 0x7fu;
          sts32(id != 0x7fu ? sb + OFF_REC + (st[i] + rk[4 * k + i]) * 4 : sb + OFF_DUMMY + lane * 4,
                w4[i] & 0xffff7fffu);
        }
      }
    }
    if (warp == kWarps - 1 &&
        __any_sync(0xffffffffu, (c4.x == 0 || c4.y == 0 || c4.z == 0 || c4.w == 0) && 4 * lane < nn)) {
      const uint32_t cz[4] = {c4.x, c4.y, c4.z, c4.w};
#pragma unroll
      for (int k = 0; k < 4; ++k) {
        uint32_t mask = __ballot_sync(0xffffffffu, cz[k] == 0 && 4 * lane + k < nn);
        while (mask) {
          const int nd = 4 * (__ffs(mask) - 1) + k;
          mask &= mask - 1;
          sts128(sb + OFF_HS + (lane >> 3) * 10240 + nd * 128 + (lane & 7) * 16, make_uint4(0, 0, 0, 0));
        }
      }
    }
    __syncwarp();
    if (lane == 0) asm volatile("mbarrier.arrive.shared::cta.b64 _, [%0];" ::"r"(barR) : "memory");
    if (tid == 0) STAMP(13);
  } else {
    bar_sync(0, kThreads);
    if (lane < 2) tma2d(sb + OFF_W2 + lane * 32768, &tmW2, lane * 64, 0, barW2);
    __syncwarp();
    en4 = lds128(sb + OFF_EN + min(lane, 23) * 16);
    if (lane >= 24) en4.x = en4.y = en4.z = en4.w;
  }

  uint32_t wp[4];
  {
    const int hb = 16 * (lane >> 1) + 4 * (lane & 1);
    const uint2 wl = lds64(sb + OFF_W1C + hb * 2), wh = lds64(sb + OFF_W1C + hb * 2 + 16);
    wp[0] = hfma2(prmt(wl.x, wh.x, 0x5410), 0x3f003f00u, 0x80008000u);
    wp[1] = hfma2(prmt(wl.x, wh.x, 0x7632), 0x3f003f00u, 0x80008000u);
    wp[2] = hfma2(prmt(wl.y, wh.y, 0x5410), 0x3f003f00u, 0x80008000u);
    wp[3] = hfma2(prmt(wl.y, wh.y, 0x7632), 0x3f003f00u, 0x80008000u);
  }
  par = lds32(sb + OFF_PAR);
  const int T = (int)__shfl_sync(0xffffffffu, en4.w, 31);
  const int s = range_start(T, warp), te = range_start(T, warp + 1);
  int node = min(kNT - 1, (int)__reduce_add_sync(0xffffffffu, (en4.x <= (uint32_t)s) + (en4.y <= (uint32_t)s) +
                                                                  (en4.z <= (uint32_t)s) + (en4.w <= (uint32_t)s)));
  bool head = (int)lds32(sb + OFF_EN - 4 + node * 4) < s;
  int pend = (int)lds32(sb + OFF_EN + node * 4);
  uint4 q = lds128(qbase + node * 128 + (((lane ^ node) & 7) << 4));
  uint32_t rp = sb + OFF_REC + s * 4;
  int left = te - s;
  mbar_wait(barR, 0);
  uint4 buf[2];
  uint32_t rc[6];
  {
    const uint2 r01 = lds64(rp);
    rc[0] = r01.x;
    rc[1] = r01.y;
  }
  buf[0] = buf[1] = make_uint4(par, 0, 0, 0);
  ldrow(buf[0], plo, phi, rc[0], left > 0);
  ldrow(buf[1], plo, phi, rc[1], left > 1);
  if (tid == 0) STAMP(6);
  if (warp != kSyncWarp) bar_sync(0, kThreads);
  if (__any_sync(0xffffffffu, ((buf[0].x ^ par) | (buf[1].x ^ par)) & 1u)) {
    ldrow(buf[0], plo, phi, rc[0], left > 0);
    ldrow(buf[1], plo, phi, rc[1], left > 1);
  }
  if (tid == 0) { STAMP(20); GSTAMP(28); }

  if (left > 0) {
    float acc[8];
#pragma unroll
    for (int c = 0; c < 8; ++c) acc[c] = 0.f;
    int rem = min(pend, te) - s;
    uint32_t a2[4] = {0, 0, 0, 0};
    while (true) {
      {
        const uint2 ra = lds64(rp + PD * 4), rb = lds64(rp + PD * 4 + 8);
        rc[PD] = ra.x;
        rc[PD + 1] = ra.y;
        rc[PD + 2] = rb.x;
        rc[PD + 3] = rb.y;
      }
#pragma unroll
      for (int u = 0; u < 4; ++u) {
        if (__any_sync(0xffffffffu, rem == u)) {
          {
            if (u > 0) {
#pragma unroll
              for (int c = 0; c < 4; ++c) {
                acc[2 * c] += lo_f(a2[c]);
                acc[2 * c + 1] += hi_f(a2[c]);
                a2[c] = 0;
              }
            }
            if (left == u) goto done;
            if (head) {
              store_side(sb, warp, lane, acc);
              head = false;
            } else {
              store_hsum(sb, node, lane, acc);
            }
#pragma unroll
            for (int c = 0; c < 8; ++c) acc[c] = 0.f;
            const int prev = pend;
            do {
              ++node;
              pend = (int)lds32(sb + OFF_EN + node * 4);
            } while (pend == prev);
            rem = min(pend, te) - prev + u;
            q = lds128(qbase + node * 128 + (((lane ^ node) & 7) << 4));
          }
        }
        const uint32_t v[4] = {buf[u % PD].x, buf[u % PD].y, buf[u % PD].z, buf[u % PD].w};
        const uint32_t e2 = prmt(rc[u], 0, 0x3232);
        uint32_t y2[4];
        y2[0] = hadd2(hfma2(e2, wp[0], v[0]), q.x);
        y2[1] = hadd2(hfma2(e2, wp[1], v[1]), q.y);
        y2[2] = hadd2(hfma2(e2, wp[2], v[2]), q.z);
        y2[3] = hadd2(hfma2(e2, wp[3], v[3]), q.w);
        asm volatile("" ::: "memory");
        ldrow(buf[u % PD], plo, phi, rc[u + PD], left > u + PD);
#pragma unroll
        for (int c = 0; c < 4; ++c) {
          const uint32_t h = hfma2(y2[c], htanh2(y2[c]), y2[c]);
          a2[c] = u == 0 ? h : hadd2(a2[c], h);
        }
      }
#pragma unroll
      for (int c = 0; c < 4; ++c) {
        acc[2 * c] += lo_f(a2[c]);
        acc[2 * c + 1] += hi_f(a2[c]);
      }
#pragma unroll
      for (int u = 0; u < PD; ++u) rc[u] = rc[u + 4];
      rp += 16;
      left -= 4;
      rem -= 4;
    }
  done:
    if (head) {
      store_side(sb, warp, lane, acc);
    } else {
      if (pend > te) {
        const int Tt = (int)lds32(sb + OFF_EN + 95 * 4), sl = range_start(Tt, lane);
        uint32_t mask = __ballot_sync(0xffffffffu, lane > warp && sl < pend && sl < range_start(Tt, lane + 1));
        while (mask) {
          const int w2i = __ffs(mask) - 1;
          mask &= mask - 1;
#pragma unroll 1
          for (int it = 0; it < (1 << 24); ++it) {
            uint32_t rdy;
            asm volatile("ld.acquire.cta.shared.u32 %0, [%1];" : "=r"(rdy) : "r"(sb + OFF_RDY + w2i * 4) : "memory");
            if (rdy) break;
          }
          const uint4 u0 = lds128(sb + OFF_SIDE + w2i * 1024 + lane * 16), u1 = lds128(sb + OFF_SIDE + w2i * 1024 + 512 + lane * 16);
          acc[0] += __uint_as_float(u0.x); acc[1] += __uint_as_float(u0.y);
          acc[2] += __uint_as_float(u0.z); acc[3] += __uint_as_float(u0.w);
          acc[4] += __uint_as_float(u1.x); acc[5] += __uint_as_float(u1.y);
          acc[6] += __uint_as_float(u1.z); acc[7] += __uint_as_float(u1.w);
        }
      }
      store_hsum(sb, node, lane, acc);
    }
  }
  if (lane == 0) STAMP(43 + (warp & 7));
  const uint32_t fm = lane < 5 ? lds32(sb + OFF_FLAG + lane * 4) : 0u;
  if (__any_sync(0xffffffffu, fm != 0)) {
    __syncthreads();
    for (int nd = warp; nd < nn; nd += kWarps) {
      const uint4 qv = lds128(qbase + nd * 128 + (((lane ^ nd) & 7) << 4));
      const uint32_t qq[4] = {qv.x, qv.y, qv.z, qv.w};
      float a[8];
      {
        const uint32_t ad = sb + OFF_HS + (lane >> 3) * 10240 + nd * 128 + (((lane & 6) ^ (nd & 7)) << 4) + ((lane & 1) << 3);
        const uint2 l = lds64(ad), h = lds64(ad ^ 16);
        a[0] = lo_f(l.x); a[2] = hi_f(l.x); a[4] = lo_f(l.y); a[6] = hi_f(l.y);
        a[1] = lo_f(h.x); a[3] = hi_f(h.x); a[5] = lo_f(h.y); a[7] = hi_f(h.y);
      }
      int extra = 0;
      for (int p = 0; p < G; ++p) {
        if (!((__shfl_sync(0xffffffffu, fm, p >> 5) >> (p & 31)) & 1u)) continue;
        int no;
        asm volatile("ld.global.cg.s32 %0, [%1];" : "=r"(no) : "l"(g_ovf_cnt + p));
        for (int i0 = 0; i0 < no; i0 += 32) {
          uint2 en = make_uint2(0xffffffffu, 0);
          if (i0 + lane < no)
            asm volatile("ld.global.cg.v2.u32 {%0,%1}, [%2];" : "=r"(en.x), "=r"(en.y) : "l"(g_ovf + p * epc + i0 + lane));
          uint32_t mask = __ballot_sync(0xffffffffu, en.x == (uint32_t)(n0 + nd));
          extra += __popc(mask);
          while (mask) {
            const int j = __ffs(mask) - 1;
            mask &= mask - 1;
            const uint32_t r = __shfl_sync(0xffffffffu, en.y, j);
            uint4 pv = make_uint4(0, 0, 0, 0);
            ldrow(pv, plo, phi, r, true);
            const uint32_t v[4] = {pv.x, pv.y, pv.z, pv.w};
            const float ef = hi_f(r);
#pragma unroll
            for (int c = 0; c < 4; ++c) {
              const float ya = fmaf(ef, lo_f(wp[c]), lo_f(qq[c])) + lo_f(v[c]);
              const float yb = fmaf(ef, hi_f(wp[c]), hi_f(qq[c])) + hi_f(v[c]);
              a[2 * c] += fmaf(ya, ftanh(ya), ya);
              a[2 * c + 1] += fmaf(yb, ftanh(yb), yb);
            }
          }
        }
      }
      if (extra) {
        store_hsum(sb, nd, lane, a);
        if (lane == 0) sts32(sb + OFF_NCNT + nd * 4, lds32(sb + OFF_NCNT + nd * 4) + extra);
      }
    }
  }
  asm volatile("fence.proxy.async.shared::cta;" ::: "memory");
  if (wg >= 2) {
    bar_arrive(0, kThreads);
  } else {
    mbar_wait(barW2, 0);
    const uint32_t da = desc_lo(sb + OFF_W2 + wg * 32768), dh = desc_lo(sb + OFF_HS);
    bar_sync(0, kThreads);
    float o[40];
    wg_fence();
    if (tid == 0) { STAMP(23); GSTAMP(29); }
#pragma unroll
    for (int k = 0; k < 16; ++k)
      wgmma_n80(o, mk_desc(da + k * 128), mk_desc(dh + (k >> 2) * (kNT * 8) + (k & 3) * 2), k);
    wg_commit();
    if (tid == 0) STAMP(24);
    const float bl = *reinterpret_cast<const float*>(sp + OFF_B2 + (64 * wg + 16 * wi + g) * 4);
    const float bh = *reinterpret_cast<const float*>(sp + OFF_B2 + (64 * wg + 16 * wi + g + 8) * 4);
    float cf[20];
#pragma unroll
    for (int j = 0; j < 10; ++j) {
      const int2 cc = *reinterpret_cast<const int2*>(sp + OFF_NCNT + (8 * j + 2 * t) * 4);
      cf[2 * j] = (float)cc.x;
      cf[2 * j + 1] = (float)cc.y;
    }
    const uint32_t stg = sb + OFF_W1B + wg * 16384;
    const uint32_t ad = stg + ((lane >> 4) * 8 + (lane & 7)) * 128 + (((2 * wi + ((lane >> 3) & 1)) ^ (lane & 7)) << 4);
    wg_wait();
    if (tid == 0) STAMP(9);
#pragma unroll
    for (int j = 0; j < 10; j += 2) {
      uint32_t r[4];
#pragma unroll
      for (int jj = 0; jj < 2; ++jj) {
        const float c0 = cf[2 * (j + jj)], c1 = cf[2 * (j + jj) + 1];
        r[2 * jj] = pack2(fmaf(c0, bl, o[4 * (j + jj)]), fmaf(c1, bl, o[4 * (j + jj) + 1]));
        r[2 * jj + 1] = pack2(fmaf(c0, bh, o[4 * (j + jj) + 2]), fmaf(c1, bh, o[4 * (j + jj) + 3]));
      }
      asm volatile("stmatrix.sync.aligned.m8n8.x4.trans.shared.b16 [%0], {%1,%2,%3,%4};" ::"r"(ad + j * 1024), "r"(r[0]),
                   "r"(r[1]), "r"(r[2]), "r"(r[3])
                   : "memory");
    }
    asm volatile("fence.proxy.async.shared::cta;" ::: "memory");
    bar_sync(2 + wg, 128);
    if ((tid & 127) == 0) {
      asm volatile("cp.async.bulk.tensor.2d.global.shared::cta.bulk_group [%0, {%1, %2}], [%3];" ::"l"(&tmO),
                   "r"(wg * 64), "r"(n0), "r"(stg)
                   : "memory");
      asm volatile("cp.async.bulk.commit_group;" ::: "memory");
      asm volatile("cp.async.bulk.wait_group.read 0;" ::: "memory");
    }
    if (tid == 0) { STAMP(10); GSTAMP(30); }
  }
}

typedef CUresult (*EncodeFn)(CUtensorMap*, CUtensorMapDataType, cuuint32_t, void*, const cuuint64_t*, const cuuint64_t*,
                             const cuuint32_t*, const cuuint32_t*, CUtensorMapInterleave, CUtensorMapSwizzle,
                             CUtensorMapL2promotion, CUtensorMapFloatOOBfill);

void make_map(EncodeFn fn, CUtensorMap* m, const void* p, uint64_t cols, uint64_t rows, uint32_t box_rows) {
  cuuint64_t dims[2] = {cols, rows};
  cuuint64_t strides[1] = {cols * 2};
  cuuint32_t box[2] = {64, box_rows};
  cuuint32_t es[2] = {1, 1};
  fn(m, CU_TENSOR_MAP_DATA_TYPE_BFLOAT16, 2, const_cast<void*>(p), dims, strides, box, es,
     CU_TENSOR_MAP_INTERLEAVE_NONE, CU_TENSOR_MAP_SWIZZLE_128B, CU_TENSOR_MAP_L2_PROMOTION_L2_256B,
     CU_TENSOR_MAP_FLOAT_OOB_FILL_NONE);
}

}

extern "C" void kernel_launch(void* const* d_in, const int* in_sizes, int n_in, void* d_out, int out_size) {
  (void)n_in;
  (void)out_size;
  static EncodeFn enc = nullptr;
  static int grid = 0;
  if (!enc) {
    void* fp = nullptr;
    cudaDriverEntryPointQueryResult qr;
    cudaGetDriverEntryPoint("cuTensorMapEncodeTiled", &fp, cudaEnableDefault, &qr);
    enc = (EncodeFn)fp;
    cudaFuncSetAttribute(mpnn_kernel, cudaFuncAttributeMaxDynamicSharedMemorySize, kSmemBytes);
    int dev = 0, sms = 0;
    cudaGetDevice(&dev);
    cudaDeviceGetAttribute(&sms, cudaDevAttrMultiProcessorCount, dev);
    grid = sms < kMaxG ? sms : kMaxG;
  }
  const int N = in_sizes[0] / 128, E = in_sizes[2];
  const int npc = (N + grid - 1) / grid;
  const uint32_t magic = (uint32_t)(((1ull << 32) + npc - 1) / npc);
  const int epc = ((E + grid - 1) / grid + 3) & ~3;
  CUtensorMap tmX, tmW1, tmW2, tmP, tmM, tmO;
  {
    void* pp = nullptr;
    cudaGetSymbolAddress(&pp, g_mbox);
    cuuint64_t dims[3] = {kCellB / 4, (cuuint64_t)kMaxG, (cuuint64_t)kMaxG};
    cuuint64_t strides[2] = {kCellB, (cuuint64_t)kCellB * kMaxG};
    cuuint32_t box[3] = {kCellB / 4, 1, (cuuint32_t)grid};
    cuuint32_t es[3] = {1, 1, 1};
    enc(&tmM, CU_TENSOR_MAP_DATA_TYPE_UINT32, 3, pp, dims, strides, box, es, CU_TENSOR_MAP_INTERLEAVE_NONE,
        CU_TENSOR_MAP_SWIZZLE_NONE, CU_TENSOR_MAP_L2_PROMOTION_NONE, CU_TENSOR_MAP_FLOAT_OOB_FILL_NONE);
  }
  uint64_t pbase;
  {
    void* pp = nullptr;
    cudaGetSymbolAddress(&pp, g_P);
    pbase = (uint64_t)pp;
    const uint64_t half = (uint64_t)kMaxN * 512;
    if ((pbase >> 32) != ((pbase + half - 1) >> 32)) pbase += half;
    make_map(enc, &tmP, (void*)pbase, 256, N, npc);
  }
  make_map(enc, &tmX, d_in[0], 128, N, kNT);
  make_map(enc, &tmW1, d_in[4], 256, 257, 128);
  make_map(enc, &tmW2, d_in[6], 128, 256, 256);
  make_map(enc, &tmO, d_out, 128, N, npc);

  mpnn_kernel<<<grid, kThreads, kSmemBytes, cudaStreamPerThread>>>(
      (const int*)d_in[3], (const int*)d_in[2], (const uint16_t*)d_in[1], E, epc, N, npc, magic,
      (const uint16_t*)d_in[4], (const uint16_t*)d_in[6], (const uint16_t*)d_in[5], (const uint16_t*)d_in[7], pbase, tmX, tmW1,
      tmW2, tmP, tmM, tmO);
}
```

```cpp
#include <cuda_runtime.h>
#include <cuda_bf16.h>
#include <cuda.h>
#include <stdint.h>

namespace {

constexpr int kNT = 80;
constexpr int kThreads = 896;
constexpr int kWarps = kThreads / 32;
constexpr int kBinThreads = 352;
constexpr int kSyncWarp = 11;
constexpr int kMaxN = 16384;
constexpr int kMaxG = 132;
constexpr int kCell = 28;
constexpr int kCellB = 128;
constexpr int kMaxE = 262144;
constexpr int kLoadThread = 320;
constexpr int kSyncLess = 4;

constexpr int OFF_W1A = 0;
constexpr int OFF_W2 = 0;
constexpr int OFF_IMG = 65536;
constexpr int OFF_REC = OFF_IMG;
constexpr int OFF_PST = OFF_IMG + 17408;
constexpr int OFF_HS = OFF_PST;
constexpr int OFF_SIDE = OFF_HS + 40960 - 1024;
constexpr int OFF_X = OFF_HS + 40960 + 7168;
constexpr int OFF_W1B = OFF_X + 20480;
constexpr int OFF_MISC = OFF_W1B + 65536;
constexpr int OFF_BAR = OFF_MISC;
constexpr int OFF_EN = OFF_MISC + 128;
constexpr int OFF_EC = OFF_EN + 96 * 8;
constexpr int OFF_NCNT = OFF_EC + 128 * 4;
constexpr int OFF_RDY = OFF_NCNT + 128 * 4;
constexpr int OFF_FLAG = OFF_RDY + 32 * 4;
constexpr int OFF_OCNT = OFF_FLAG + 32;
constexpr int OFF_B2 = OFF_OCNT + 168 * 4;
constexpr int OFF_W1C = OFF_B2 + 512;
constexpr int OFF_PAR = OFF_W1C + 512;
constexpr int OFF_RS = OFF_PAR + 16;
constexpr int OFF_DUMMY = OFF_RS + 144;
constexpr int OFF_LUT = OFF_DUMMY + 128;
constexpr int kLutLo = 0x3980, kLutN = 0x4080 - kLutLo;
constexpr int kSmemBytes = OFF_LUT + kLutN;
static_assert(kSmemBytes <= 232448, "smem");
static_assert(kMaxG * 4 <= kThreads - 32, "mailbox mapping");
static_assert(OFF_SIDE + kWarps * 1024 <= OFF_W1B && OFF_X % 1024 == 0 && OFF_W1B % 1024 == 0, "side rows");
static_assert(OFF_DUMMY % 16 == 0 && OFF_EN % 16 == 0 && OFF_NCNT % 16 == 0 && OFF_B2 % 16 == 0 && OFF_W1C % 16 == 0, "align");

__device__ uint4 g_P[((2 << 24) + kMaxN * 256) / 16];
__device__ uint4 g_mbox[kMaxG * kMaxG * kCellB / 16];
__device__ uint2 g_ovf[kMaxE];
__device__ int g_ovf_cnt[kMaxG];
__device__ unsigned int g_bar[128];

__device__ __forceinline__ uint32_t prmt(uint32_t a, uint32_t b, uint32_t s) {
  uint32_t d;
  asm("prmt.b32 %0,%1,%2,%3;" : "=r"(d) : "r"(a), "r"(b), "r"(s));
  return d;
}
__device__ __forceinline__ uint32_t hfma2(uint32_t a, uint32_t b, uint32_t c) {
  uint32_t d;
  asm("fma.rn.bf16x2 %0,%1,%2,%3;" : "=r"(d) : "r"(a), "r"(b), "r"(c));
  return d;
}
__device__ __forceinline__ uint32_t hfma2_hi(uint32_t a, uint32_t b, uint32_t c) {
  uint32_t d;
  asm("{.reg .b16 l, h; .reg .b32 e; mov.b32 {l, h}, %1; mov.b32 e, {h, h}; fma.rn.bf16x2 %0, e, %2, %3;}"
      : "=r"(d)
      : "r"(a), "r"(b), "r"(c));
  return d;
}
__device__ __forceinline__ uint32_t hadd2(uint32_t a, uint32_t b) {
  uint32_t d;
  asm("add.rn.bf16x2 %0,%1,%2;" : "=r"(d) : "r"(a), "r"(b));
  return d;
}
__device__ __forceinline__ uint32_t htanh2(uint32_t a) {
  uint32_t d;
  asm("tanh.approx.bf16x2 %0,%1;" : "=r"(d) : "r"(a));
  return d;
}
__device__ __forceinline__ float ftanh(float x) {
  float y;
  asm("tanh.approx.f32 %0,%1;" : "=f"(y) : "f"(x));
  return y;
}
__device__ __forceinline__ uint32_t pack2(float lo, float hi) {
  uint32_t d;
  asm("cvt.rn.bf16x2.f32 %0,%1,%2;" : "=r"(d) : "f"(hi), "f"(lo));
  return d;
}
__device__ __forceinline__ float lo_f(uint32_t v) { return __uint_as_float(prmt(v, 0, 0x1044)); }
__device__ __forceinline__ float hi_f(uint32_t v) { return __uint_as_float(v & 0xffff0000u); }

__device__ __forceinline__ void mbar_init(uint32_t bar, uint32_t cnt) {
  asm volatile("mbarrier.init.shared::cta.b64 [%0], %1;" ::"r"(bar), "r"(cnt) : "memory");
}
__device__ __forceinline__ void mbar_expect(uint32_t bar, uint32_t bytes) {
  asm volatile("mbarrier.arrive.expect_tx.shared::cta.b64 _, [%0], %1;" ::"r"(bar), "r"(bytes) : "memory");
}
__device__ __forceinline__ void mbar_wait(uint32_t bar, uint32_t parity) {
  uint32_t ok = 0;
#pragma unroll 1
  for (int it = 0; it < (1 << 15) && !ok; ++it) {
    asm volatile(
        "{.reg .pred p; mbarrier.try_wait.parity.shared::cta.b64 p, [%1], %2, %3; selp.u32 %0, 1, 0, p;}"
        : "=r"(ok)
        : "r"(bar), "r"(parity), "r"(20000u)
        : "memory");
  }
}
__device__ __forceinline__ void tma2d(uint32_t dst, const CUtensorMap* m, int c0, int c1, uint32_t bar) {
  asm volatile(
      "cp.async.bulk.tensor.2d.shared::cluster.global.mbarrier::complete_tx::bytes [%0], [%1, {%2, %3}], [%4];" ::"r"(dst),
      "l"(m), "r"(c0), "r"(c1), "r"(bar)
      : "memory");
}
__device__ __forceinline__ void bar_sync(int id, int n) { asm volatile("bar.sync %0, %1;" ::"r"(id), "r"(n) : "memory"); }
__device__ __forceinline__ void bar_arrive(int id, int n) {
  asm volatile("bar.arrive %0, %1;" ::"r"(id), "r"(n) : "memory");
}
__device__ __forceinline__ bool bar_or(int id, int n, bool v) {
  uint32_t r;
  asm volatile("{.reg .pred p, q; setp.ne.u32 p, %3, 0; bar.red.or.pred q, %1, %2, p; selp.u32 %0, 1, 0, q;}"
               : "=r"(r)
               : "r"(id), "r"(n), "r"((uint32_t)v)
               : "memory");
  return r != 0;
}
__device__ __forceinline__ uint32_t desc_lo(uint32_t addr) { return ((addr & 0x3FFFF) >> 4) | (1u << 16); }
__device__ __forceinline__ uint64_t mk_desc(uint32_t lo) {
  return (uint64_t)lo | ((64ull | (1ull << 30)) << 32);
}
__device__ __forceinline__ uint32_t atoms_inc(uint32_t a) {
  uint32_t r;
  asm volatile("atom.shared.add.u32 %0, [%1], 1;" : "=r"(r) : "r"(a) : "memory");
  return r;
}

__device__ __forceinline__ void wgmma_n80(float (&d)[40], uint64_t da, uint64_t db, int acc) {
  asm volatile(
      "{.reg .pred p; setp.ne.b32 p, %42, 0;\n"
      "wgmma.mma_async.sync.aligned.m64n80k16.f32.bf16.bf16 "
      "{%0,%1,%2,%3,%4,%5,%6,%7,%8,%9,%10,%11,%12,%13,%14,%15,%16,%17,%18,%19,"
      "%20,%21,%22,%23,%24,%25,%26,%27,%28,%29,%30,%31,%32,%33,%34,%35,%36,%37,%38,%39},"
      "%40, %41, p, 1, 1, 1, 0;}\n"
      : "+f"(d[0]), "+f"(d[1]), "+f"(d[2]), "+f"(d[3]), "+f"(d[4]), "+f"(d[5]), "+f"(d[6]), "+f"(d[7]), "+f"(d[8]),
        "+f"(d[9]), "+f"(d[10]), "+f"(d[11]), "+f"(d[12]), "+f"(d[13]), "+f"(d[14]), "+f"(d[15]), "+f"(d[16]),
        "+f"(d[17]), "+f"(d[18]), "+f"(d[19]), "+f"(d[20]), "+f"(d[21]), "+f"(d[22]), "+f"(d[23]), "+f"(d[24]),
        "+f"(d[25]), "+f"(d[26]), "+f"(d[27]), "+f"(d[28]), "+f"(d[29]), "+f"(d[30]), "+f"(d[31]), "+f"(d[32]),
        "+f"(d[33]), "+f"(d[34]), "+f"(d[35]), "+f"(d[36]), "+f"(d[37]), "+f"(d[38]), "+f"(d[39])
      : "l"(da), "l"(db), "r"(acc)
      : "memory");
}
__device__ __forceinline__ void wg_fence() { asm volatile("wgmma.fence.sync.aligned;" ::: "memory"); }
__device__ __forceinline__ void wg_commit() { asm volatile("wgmma.commit_group.sync.aligned;" ::: "memory"); }
__device__ __forceinline__ void wg_wait() { asm volatile("wgmma.wait_group.sync.aligned 0;" ::: "memory"); }

__device__ __forceinline__ uint4 lds128(uint32_t a) {
  uint4 v;
  asm volatile("ld.shared.v4.u32 {%0,%1,%2,%3}, [%4];" : "=r"(v.x), "=r"(v.y), "=r"(v.z), "=r"(v.w) : "r"(a));
  return v;
}
__device__ __forceinline__ uint2 lds64(uint32_t a) {
  uint2 v;
  asm volatile("ld.shared.v2.u32 {%0,%1}, [%2];" : "=r"(v.x), "=r"(v.y) : "r"(a));
  return v;
}
__device__ __forceinline__ uint32_t lds32(uint32_t a) {
  uint32_t v;
  asm volatile("ld.shared.u32 %0, [%1];" : "=r"(v) : "r"(a));
  return v;
}
__device__ __forceinline__ void sts128(uint32_t a, uint4 v) {
  asm volatile("st.shared.v4.u32 [%0], {%1,%2,%3,%4};" ::"r"(a), "r"(v.x), "r"(v.y), "r"(v.z), "r"(v.w) : "memory");
}
__device__ __forceinline__ void sts32(uint32_t a, uint32_t x) {
  asm volatile("st.shared.u32 [%0], %1;" ::"r"(a), "r"(x) : "memory");
}
__device__ __forceinline__ void ldrow(uint4& v, uint64_t& a, uint32_t plo, uint32_t r, bool pred) {
  asm volatile(
      "{.reg .pred p; .reg .b32 l, h; setp.ne.b32 p, %6, 0; mov.b64 {l, h}, %4; mov.b64 %4, {%5, h};\n"
      "@p ld.relaxed.gpu.global.v4.u32 {%0,%1,%2,%3}, [%4];}"
      : "+r"(v.x), "+r"(v.y), "+r"(v.z), "+r"(v.w), "+l"(a)
      : "r"(prmt(r, plo, 0x7104)), "r"((int)pred));
}

__device__ __forceinline__ void store_hsum(uint32_t ad, const float (&a)[8]) {
  sts128(ad, make_uint4(pack2(a[0], a[1]), pack2(a[2], a[3]), pack2(a[4], a[5]), pack2(a[6], a[7])));
}
__device__ __forceinline__ void stsm_t(uint32_t ad, uint32_t r0, uint32_t r1, uint32_t r2, uint32_t r3) {
  asm volatile("stmatrix.sync.aligned.m8n8.x4.trans.shared.b16 [%0], {%1,%2,%3,%4};" ::"r"(ad), "r"(r0), "r"(r1), "r"(r2),
               "r"(r3)
               : "memory");
}

__device__ __forceinline__ void store_side(uint32_t sb, int warp, int lane, const float (&a)[8]) {
  const uint32_t ad = sb + OFF_SIDE + warp * 1024 + lane * 16;
  sts128(ad, make_uint4(__float_as_uint(a[0]), __float_as_uint(a[1]), __float_as_uint(a[2]), __float_as_uint(a[3])));
  sts128(ad + 512, make_uint4(__float_as_uint(a[4]), __float_as_uint(a[5]), __float_as_uint(a[6]), __float_as_uint(a[7])));
  __syncwarp();
  asm volatile("st.release.cta.shared.u32 [%0], 1;" ::"r"(sb + OFF_RDY + warp * 4) : "memory");
}
__device__ __forceinline__ int range_start(int T, int w) {
  const int d = T >= 2 * kSyncLess * kWarps ? kSyncLess : 0;
  constexpr int K = 65536 / (2 * kWarps);
  return w >= kWarps ? T : 2 * (((T + d) * w * K + 32768) >> 16) - (w > kSyncWarp ? d : 0);
}

__global__ void __launch_bounds__(kThreads, 1)
mpnn_kernel(const int* __restrict__ dst, const int* __restrict__ src, const uint16_t* __restrict__ e_attr, int E,
            int epc, int N, int npc, uint32_t npc_magic, const uint16_t* __restrict__ w1,
            const uint16_t* __restrict__ w2, const uint16_t* __restrict__ b1, const uint16_t* __restrict__ b2, uint64_t pbase, uint16_t* __restrict__ out,
            const __grid_constant__ CUtensorMap tmX,
            const __grid_constant__ CUtensorMap tmW2, const __grid_constant__ CUtensorMap tmP,
            const __grid_constant__ CUtensorMap tmM, const __grid_constant__ CUtensorMap tmMi, const __grid_constant__ CUtensorMap tmWB) {
  extern __shared__ __align__(1024) uint8_t smem_raw[];
  const int tid = threadIdx.x, b = blockIdx.x;
  const int e0 = b * epc, e1 = min(E, e0 + epc);
  int4 dv = make_int4(-1, -1, -1, -1), sv = make_int4(0, 0, 0, 0);
  uint2 ev = make_uint2(0, 0);
  if (tid < kBinThreads && e0 + 4 * tid + 3 < e1) {
    dv = *reinterpret_cast<const int4*>(dst + e0 + 4 * tid);
    sv = *reinterpret_cast<const int4*>(src + e0 + 4 * tid);
    ev = *reinterpret_cast<const uint2*>(e_attr + e0 + 4 * tid);
  }
  const int n0 = b * npc, nn = max(0, min(npc, N - n0));
  if ((tid >> 1) == kSyncWarp * 16)
    asm volatile("cp.async.ca.shared.global [%0], [%1], 4;" ::"r"(1024 + OFF_PAR + 8 + (tid & 1) * 4), "l"(g_bar + (tid & 1) * 64)
                 : "memory");
  if (tid == kLoadThread) {
    constexpr uint32_t bar = 1024 + OFF_BAR;
    mbar_init(bar, 1);
    mbar_init(bar + 16, 1);
    asm volatile("fence.mbarrier_init.release.cluster;" ::: "memory");
    mbar_expect(bar + 16, 65536);
    asm volatile(
        "cp.async.bulk.tensor.3d.shared::cluster.global.mbarrier::complete_tx::bytes [%0], [%1, {0, 0, 0}], [%2];" ::"r"(
            1024 + OFF_W1A),
        "l"(&tmWB), "r"(bar + 16)
        : "memory");
    mbar_expect(bar, 2 * kNT * 128);
    __nanosleep(100);
    asm volatile(
        "cp.async.bulk.tensor.3d.shared::cluster.global.mbarrier::complete_tx::bytes [%0], [%1, {0, %3, 0}], [%2];" ::"r"(
            1024 + OFF_X),
        "l"(&tmX), "r"(bar), "r"(n0)
        : "memory");
  }
  uint32_t par = 0;
  constexpr uint32_t sb = 1024;
  if ((uint32_t)__cvta_generic_to_shared(smem_raw) != sb) __trap();
  const uint8_t* const sp = smem_raw;
  const int lane = tid & 31;
  const int warp = __shfl_sync(0xffffffffu, tid >> 5, 0);
  const int wg = warp >> 2, wi = warp & 3;
  const int G = gridDim.x;
  const uint32_t barX = sb + OFF_BAR, barW2 = barX + 8, barM = barX + 80, barR = barX + 88;
  const int g = lane >> 2, t = lane & 3;

  if (warp == kSyncWarp) {
    if (lane == 0) {
      mbar_init(barX + 24, 1);
      mbar_init(barW2, 1);
      mbar_init(barM, 1);
      mbar_init(barR, 1);
      asm volatile("fence.mbarrier_init.release.cluster;" ::: "memory");
      mbar_expect(barX + 24, 65536);
      mbar_expect(barW2, 65536);
      mbar_expect(barM, G * kCellB);
    }
    __syncwarp();
    asm volatile("cp.async.cg.shared.global [%0], [%1], 16;" ::"r"(sb + OFF_W1C + lane * 16), "l"(w1 + 256 * 256 + lane * 8) : "memory");
    if (lane < 16)
      asm volatile("cp.async.cg.shared.global [%0], [%1], 16;" ::"r"(sb + OFF_B2 + lane * 16), "l"(b2 + lane * 8) : "memory");
    asm volatile("cp.async.commit_group;" ::: "memory");
    if (lane == 0) {
      if (b < 128) {
        const uint16_t* pf = b < 64 ? w1 + 128 * 256 + b * 512 : w2 + (b - 64) * 512;
        asm volatile("cp.async.bulk.prefetch.L2.global [%0], 1024;" ::"l"(pf) : "memory");
      }
      asm volatile("prefetch.tensormap [%0];" ::"l"(&tmM) : "memory");
      asm volatile("prefetch.tensormap [%0];" ::"l"(&tmMi) : "memory");
      asm volatile("prefetch.tensormap [%0];" ::"l"(&tmWB) : "memory");
      asm volatile("prefetch.tensormap [%0];" ::"l"(&tmP) : "memory");
      asm volatile("prefetch.tensormap [%0];" ::"l"(&tmW2) : "memory");
    }
    bar_arrive(13, 512 + 64);
    bar_sync(1, kBinThreads + 32);
    if (lane == 0) {
      asm volatile("cp.async.bulk.tensor.3d.global.shared::cta.bulk_group [%0, {0, %1, 0}], [%2];" ::"l"(&tmM), "r"(b),
                   "r"(sb + OFF_IMG)
                   : "memory");
      asm volatile("cp.async.bulk.commit_group;" ::: "memory");
      asm volatile("cp.async.bulk.wait_group.read 0;" ::: "memory");
      asm volatile(
          "cp.async.bulk.tensor.3d.shared::cluster.global.mbarrier::complete_tx::bytes [%0], [%1, {0, 128, 0}], [%2];" ::"r"(
              sb + OFF_W1B),
          "l"(&tmWB), "r"(barX + 24)
          : "memory");
    }
    __syncwarp();
    bar_arrive(6, 512 + 32);
    sts32(sb + OFF_RDY + lane * 4, 0);
    asm volatile("cp.async.wait_group 0;" ::: "memory");
    __syncwarp();
    par = lds32(sb + OFF_PAR + 8 + (lane & 1) * 4) < (uint32_t)G ? 1u : 0u;
    sts32(sb + OFF_PAR, par);
    bar_arrive(14, 512 + 32);
    if (lane == 0) {
      asm volatile("cp.async.bulk.wait_group 0;" ::: "memory");
      asm volatile("fence.acq_rel.gpu;" ::: "memory");
      asm volatile("red.relaxed.gpu.global.inc.u32 [%0], %1;" ::"l"(g_bar), "r"(2 * G - 1) : "memory");
      uint32_t v;
      int it = 0;
      do {
        asm volatile("ld.relaxed.gpu.global.u32 %0, [%1];" : "=r"(v) : "l"(g_bar) : "memory");
      } while (((v < (uint32_t)G) == (par != 0)) && ++it < (1 << 20));
      asm volatile(
          "cp.async.bulk.tensor.3d.shared::cluster.global.mbarrier::complete_tx::bytes [%0], [%1, {0, 0, %3}], [%2];" ::"r"(
              sb + OFF_IMG),
          "l"(&tmMi), "r"(barM), "r"(b)
          : "memory");
    }
    __syncwarp();
    bar_sync(9, 512 + 32);
    if (lane == 0) {
      asm volatile("cp.async.bulk.tensor.4d.global.shared::cta.bulk_group [%0, {0, %1, 0, 0}], [%2];" ::"l"(&tmP), "r"(n0),
                   "r"(sb + OFF_PST)
                   : "memory");
      asm volatile("cp.async.bulk.commit_group;" ::: "memory");
      tma2d(sb + OFF_W2, &tmW2, 0, 0, barW2);
      tma2d(sb + OFF_W2 + 32768, &tmW2, 64, 0, barW2);
      asm volatile("cp.async.bulk.wait_group 0;" ::: "memory");
      asm volatile("red.relaxed.gpu.global.inc.u32 [%0], %1;" ::"l"(g_bar + 64), "r"(2 * G - 1) : "memory");
    }
    __syncwarp();
    {
#pragma unroll 1
      for (int it = 0; it < (1 << 20); ++it) {
        uint32_t v;
        asm volatile("ld.relaxed.gpu.global.u32 %0, [%1];" : "=r"(v) : "l"(g_bar + 64) : "memory");
        if ((v < (uint32_t)G) != (par != 0) || (int)(par ? v : v - G) >= G - (G >> 1)) break;
      }
      bar_arrive(10, kThreads);
      mbar_wait(barR, 0);
    }
  } else if (warp < kSyncWarp) {
    const int bt = tid;
    if (warp == kLoadThread / 32) { __syncwarp(); bar_arrive(13, 512 + 64); }
    if (bt < 34) sts128(sb + OFF_OCNT + bt * 16, make_uint4(0, 0, 0, 0));
    else if (bt < 58) sts128(sb + OFF_NCNT + (bt - 34) * 16, make_uint4(0, 0, 0, 0));
    else if (bt < 60) sts128(sb + OFF_FLAG + (bt - 58) * 16, make_uint4(0, 0, 0, 0));
    else if (bt == 60) sts32(sb + OFF_EN - 8, 0);
    else if (bt == 61) sts32(sb + OFF_EC - 4, 0);
    if (bt < kMaxG) sts128(sb + OFF_IMG + bt * kCellB + (112 ^ ((bt & 7) << 4)), make_uint4(~0u, ~0u, ~0u, ~0u));
    bar_sync(12, kBinThreads);
    bool spilled = false;
    for (int e = e0 + 4 * bt;;) {
      if (e < e1 && e + 3 >= e1) {
        dv.x = dst[e]; sv.x = src[e]; ev.x = e_attr[e];
        if (e + 1 < e1) { dv.y = dst[e + 1]; sv.y = src[e + 1]; ev.x |= (uint32_t)e_attr[e + 1] << 16; }
        if (e + 2 < e1) { dv.z = dst[e + 2]; sv.z = src[e + 2]; ev.y = e_attr[e + 2]; }
      }
      const int d4[4] = {dv.x, dv.y, dv.z, dv.w};
      const int s4[4] = {sv.x, sv.y, sv.z, sv.w};
      uint32_t ow[4], pos[4];
#pragma unroll
      for (int i = 0; i < 4; ++i) {
        ow[i] = d4[i] >= 0 ? __umulhi((uint32_t)d4[i], npc_magic) : 136 + lane;
        pos[i] = atoms_inc(sb + OFF_OCNT + ow[i] * 4);
      }
      bool over = false;
#pragma unroll
      for (int i = 0; i < 4; ++i) {
        const bool ok = d4[i] >= 0 && pos[i] < kCell;
        over |= d4[i] >= 0 && pos[i] >= kCell;
        const uint32_t cell = sb + OFF_IMG + ow[i] * kCellB + ((ow[i] & 7) << 4);
        const uint32_t c = (s4[i] - ow[i]) * npc + d4[i];
        sts32(ok ? cell ^ (pos[i] * 4) : sb + OFF_DUMMY + lane * 4, prmt(c, i < 2 ? ev.x : ev.y, (i & 1) ? 0x7610 : 0x5410));
        asm volatile("red.shared.xor.b32 [%0], %1;" ::"r"(ok ? cell ^ (112 + (pos[i] >> 3) * 4) : sb + OFF_DUMMY + lane * 4),
                     "r"(((c >> 16) ^ 15u) << ((pos[i] & 7) * 4))
                     : "memory");
      }
      const uint32_t r4[4] = {prmt(sv.x, ev.x, 0x5410), prmt(sv.y, ev.x, 0x7610), prmt(sv.z, ev.y, 0x5410),
                              prmt(sv.w, ev.y, 0x7610)};
      if (over) {
        spilled = true;
#pragma unroll 1
        for (int i = 0; i < 4; ++i) {
          const uint32_t ps = i == 0 ? pos[0] : i == 1 ? pos[1] : i == 2 ? pos[2] : pos[3];
          const int dd = i == 0 ? d4[0] : i == 1 ? d4[1] : i == 2 ? d4[2] : d4[3];
          if (dd >= 0 && ps >= kCell)
            g_ovf[e0 + atoms_inc(sb + OFF_FLAG + 20)] =
                make_uint2((uint32_t)dd, i == 0 ? r4[0] : i == 1 ? r4[1] : i == 2 ? r4[2] : r4[3]);
        }
      }
      e += 4 * kBinThreads;
      if (e - 4 * bt >= e1) break;
      dv = make_int4(-1, -1, -1, -1);
      if (e + 3 < e1) {
        dv = *reinterpret_cast<const int4*>(dst + e);
        sv = *reinterpret_cast<const int4*>(src + e);
        ev = *reinterpret_cast<const uint2*>(e_attr + e);
      }
    }
    if (bar_or(12, kBinThreads, spilled)) {
      if (bt == 0) g_ovf_cnt[b] = (int)lds32(sb + OFF_FLAG + 20);
      if (bt < G && lds32(sb + OFF_OCNT + bt * 4) > kCell)
        asm volatile("st.shared.u16 [%0], %1;" ::"r"(sb + OFF_IMG + bt * kCellB + (126 ^ ((bt & 7) << 4))), "h"((uint16_t)0xfff0) : "memory");
      __threadfence();
      asm volatile("fence.proxy.async;" ::: "memory");
    }
    asm volatile("fence.proxy.async.shared::cta;" ::: "memory");
    bar_sync(1, kBinThreads + 32);

    uint4 mw[4];
    uint32_t md[4], rk[16], id[16];
    const uint32_t cp = sb + OFF_IMG + (bt >> 2) * kCellB + (((bt >> 2) & 7) << 4);
    const bool has1 = bt + kBinThreads < 4 * G;
    mbar_wait(barM, 0);
#pragma unroll
    for (int k = 0; k < 4; ++k) {
      md[k] = 0xffffu;
      if ((k & 1) ? has1 : bt < 4 * G)
        asm volatile("ld.shared.u16 %0, [%1];"
                     : "=r"(md[k])
                     : "r"((cp ^ (112 + (bt & 3) * 2 + (k >> 1) * 8)) + (k & 1) * (kBinThreads / 4) * kCellB));
    }
    mw[0] = lds128(cp ^ ((bt & 3) * 16));
    mw[1] = lds128((cp ^ ((bt & 3) * 16)) + (kBinThreads / 4) * kCellB);
    bool any[4];
    any[0] = true;
    any[1] = warp * 32 + kBinThreads < 4 * G;
    any[2] = __any_sync(0xffffffffu, md[2] != 0xffffu);
    any[3] = __any_sync(0xffffffffu, md[3] != 0xffffu);
#pragma unroll
    for (int k = 0; k < 4; ++k) {
      if (any[k]) {
        if (k >= 2) {
          mw[k] = lds128((cp ^ ((bt & 3) * 16 + 64)) + (k & 1) * (kBinThreads / 4) * kCellB);
          if ((bt & 3) == 3) {
            if (md[k] != 0xffffu) {
              const int p = (bt + (k - 2) * kBinThreads) >> 2;
              asm volatile("red.shared.or.b32 [%0], %1;" ::"r"(sb + OFF_FLAG + (p >> 5) * 4), "r"(1u << (p & 31)) : "memory");
            }
            md[k] = 0xffffu;
          }
        }
        uint32_t w4[4] = {mw[k].x, mw[k].y, mw[k].z, mw[k].w};
#pragma unroll
        for (int i = 0; i < 4; ++i) {
          const uint32_t nb = (md[k] >> (4 * i)) & 15u;
          const uint32_t c = prmt(w4[i], nb, 0x5410), sr = __umulhi(c, npc_magic);
          id[4 * k + i] = nb != 15u ? c - sr * npc : 96 + lane;
          w4[i] = prmt(sr, w4[i], 0x7610);
          rk[4 * k + i] = atoms_inc(sb + OFF_NCNT + id[4 * k + i] * 4);
        }
        mw[k] = make_uint4(w4[0], w4[1], w4[2], w4[3]);
      }
    }
    bar_sync(12, kBinThreads);
    const uint4 c4 = lane < 24 ? lds128(sb + OFF_NCNT + lane * 16) : make_uint4(0, 0, 0, 0);
    {
      const uint32_t tot = c4.x + c4.y + c4.z + c4.w;
      uint32_t v = tot;
#pragma unroll
      for (int o = 1; o < 32; o <<= 1) {
        const uint32_t u = __shfl_up_sync(0xffffffffu, v, o);
        if (lane >= o) v += u;
      }
      const uint32_t x0 = lane * 512 + (lane & 1) * 64;
      sts128(sb + OFF_EC + lane * 16, make_uint4(v - tot + c4.x, v - c4.z - c4.w, v - c4.w, v));
      if (warp == kSyncWarp - 1) {
        const int T = (int)__shfl_sync(0xffffffffu, v, 31);
        sts32(sb + OFF_RS + lane * 4, range_start(T, lane));
        sts32(sb + OFF_RS + 128, T);
      }
      if (warp == kSyncWarp - 2 && lane < 24) {
        sts128(sb + OFF_EN + lane * 32, make_uint4(v - tot + c4.x, x0, v - c4.z - c4.w, x0 + 144));
        sts128(sb + OFF_EN + lane * 32 + 16, make_uint4(v - c4.w, x0 + 288, v, lane == 23 ? 0 : x0 + 432));
      }
      __syncwarp();
    }
#pragma unroll
    for (int k = 0; k < 4; ++k) {
      if (any[k]) {
        uint32_t st[4];
#pragma unroll
        for (int i = 0; i < 4; ++i) st[i] = lds32(sb + OFF_EC - 4 + id[4 * k + i] * 4);
        const uint32_t w4[4] = {mw[k].x, mw[k].y, mw[k].z, mw[k].w};
#pragma unroll
        for (int i = 0; i < 4; ++i)
          sts32(id[4 * k + i] < 96 ? sb + OFF_REC + (st[i] + rk[4 * k + i]) * 4 : sb + OFF_DUMMY + lane * 4, w4[i]);
      }
    }
  } else {
    const int m = wg - 3;
    const uint32_t barA = barX + 16, barB = barX + 24;
    const uint32_t sa = sb + OFF_W1A + m * 16384, sq = sb + OFF_W1B + m * 16384;
    const float bl = 0.5f * __uint_as_float((uint32_t)b1[64 * m + 16 * wi + g] << 16);
    const float bh = 0.5f * __uint_as_float((uint32_t)b1[64 * m + 16 * wi + g + 8] << 16);
    bar_sync(13, 512 + 64);
#pragma unroll
    for (int i = 0; i < 4; ++i) {
      const int k = tid - 384 + 512 * i;
      if (k < kLutN)
        asm volatile("st.shared.u8 [%0], %1;" ::"r"(sb + OFF_LUT + k),
                     "r"(kLutLo + k - pack2(ftanh(__uint_as_float((uint32_t)(kLutLo + k) << 16)), 0.f))
                     : "memory");
    }
    const int srow = (lane >> 4) * 8 + (lane & 7), schunk = 2 * wi + ((lane >> 3) & 1);
    const uint32_t dx = desc_lo(sb + OFF_X);
    float acc[40];
    mbar_wait(barA, 0);
    mbar_wait(barX, 0);
    bar_sync(6, 512 + 32);
    wg_fence();
#pragma unroll
    for (int k = 0; k < 8; ++k)
      wgmma_n80(acc, mk_desc(desc_lo(sa) + k * 128), mk_desc(dx + (k >> 2) * (kNT * 8) + (k & 3) * 2), k);
    wg_commit();
    bar_sync(14, 512 + 32);
    par = lds32(sb + OFF_PAR);
    wg_wait();
    const uint32_t keep = g == 0 ? 0xfffefffeu : 0xffffffffu, tag = (par * 0x10001u) & ~keep;
    const int r0 = m * npc + srow;
    const uint32_t pa = sb + OFF_PST + r0 * 128 + ((schunk ^ (r0 & 7)) << 4);
#pragma unroll
    for (int j = 0; j < 10; j += 2) {
      uint32_t r[4];
#pragma unroll
      for (int i = 0; i < 4; ++i)
        r[i] = (hfma2(pack2(acc[4 * j + 2 * i], acc[4 * j + 2 * i + 1]), 0x3f003f00u, 0x80008000u) & keep) | tag;
      stsm_t(j < 8 || 64 + srow < npc ? pa + j * 1024 : sb + OFF_DUMMY + (lane & 7) * 16, r[0], r[1], r[2], r[3]);
    }
    asm volatile("fence.proxy.async.shared::cta;" ::: "memory");
    bar_arrive(9, 512 + 32);
    mbar_wait(barB, 0);
    wg_fence();
#pragma unroll
    for (int k = 0; k < 8; ++k)
      wgmma_n80(acc, mk_desc(desc_lo(sq) + k * 128), mk_desc(dx + (k >> 2) * (kNT * 8) + (k & 3) * 2), k);
    wg_commit();
    wg_wait();
    bar_sync(2 + m, 128);
#pragma unroll
    for (int j = 0; j < 10; j += 2) {
      uint32_t r[4];
#pragma unroll
      for (int i = 0; i < 4; ++i) {
        const float bb = (i & 1) ? bh : bl;
        r[i] = pack2(fmaf(acc[4 * j + 2 * i], 0.5f, bb), fmaf(acc[4 * j + 2 * i + 1], 0.5f, bb));
      }
      stsm_t(sq + srow * 128 + ((schunk ^ (lane & 7)) << 4) + j * 1024, r[0], r[1], r[2], r[3]);
    }
  }
  const uint64_t pl64 = pbase + ((uint64_t)(lane >> 4) << 24) + (lane & 15) * 16;
  const uint32_t plo = (uint32_t)pl64;

  if (warp != kSyncWarp) {
    bar_sync(15, kThreads - 32);
    if (tid == kThreads - 1) asm volatile("mbarrier.arrive.shared::cta.b64 _, [%0];" ::"r"(barR) : "memory");
  }
  par = lds32(sb + OFF_PAR);
  const int s = (int)lds32(sb + OFF_RS + warp * 4), te = (int)lds32(sb + OFF_RS + warp * 4 + 4);
  uint32_t rp = sb + OFF_REC + s * 4;
  int left = te - s;
  const uint32_t zero = lds32(sb + OFF_EN - 8);
  uint64_t pa[2];
  pa[0] = pa[1] = pl64 + ((uint64_t)zero << 32);
  uint4 buf[2];
  uint32_t rc[6];
  {
    const uint2 r01 = lds64(rp);
    rc[0] = r01.x;
    rc[1] = r01.y;
  }
  buf[0] = buf[1] = make_uint4(par, 0, 0, 0);
  if (warp != kSyncWarp) bar_sync(10, kThreads);
  ldrow(buf[0], pa[0], plo, rc[0], left > 0);
  ldrow(buf[1], pa[1], plo, rc[1], left > 1);
  if (warp == kSyncWarp - 1) {
    const uint4 c4 = lane < 24 ? lds128(sb + OFF_NCNT + lane * 16) : make_uint4(1, 1, 1, 1);
    if (__any_sync(0xffffffffu, (c4.x == 0 || c4.y == 0 || c4.z == 0 || c4.w == 0) && 4 * lane < nn)) {
      const uint32_t cz[4] = {c4.x, c4.y, c4.z, c4.w};
#pragma unroll
      for (int k = 0; k < 4; ++k) {
        uint32_t mask = __ballot_sync(0xffffffffu, cz[k] == 0 && 4 * lane + k < nn);
        while (mask) {
          const int nd = 4 * (__ffs(mask) - 1) + k;
          mask &= mask - 1;
          sts128(sb + OFF_HS + (lane >> 3) * 10240 + nd * 128 + (lane & 7) * 16, make_uint4(0, 0, 0, 0));
        }
      }
    }
  }
  const uint4 en4 = lds128(sb + OFF_EC + lane * 16);
  uint32_t wp[4];
  {
    const uint4 w = lds128(sb + OFF_W1C + lane * 16);
    wp[0] = hfma2(w.x, 0x3f003f00u, 0x80008000u);
    wp[1] = hfma2(w.y, 0x3f003f00u, 0x80008000u);
    wp[2] = hfma2(w.z, 0x3f003f00u, 0x80008000u);
    wp[3] = hfma2(w.w, 0x3f003f00u, 0x80008000u);
  }
  uint32_t np = sb + OFF_EN +
                8 * min(kNT - 1, (int)__reduce_add_sync(0xffffffffu, (en4.x <= (uint32_t)s) + (en4.y <= (uint32_t)s) +
                                                                         (en4.z <= (uint32_t)s) + (en4.w <= (uint32_t)s)));
  uint32_t mode = (int)lds32(np - 8) < s ? 1u : 0u;
  int pend;
  uint32_t nx;
  {
    const uint2 e = lds64(np);
    pend = (int)e.x;
    nx = e.y;
  }
  const uint32_t ql = (lane >> 3) * 16384 + (lane & 7) * 16 + zero;
  const uint32_t hl = sb + OFF_HS + (lane >> 3) * 10240 + zero, l6 = (lane & 7) * 16 + zero;
  uint4 q = lds128(sb + OFF_W1B + (ql ^ nx));
#pragma unroll 1
  for (int it = 0; it < (1 << 16) && __any_sync(0xffffffffu, ((buf[0].x ^ par) | (buf[1].x ^ par)) & 1u); ++it) {
    ldrow(buf[0], pa[0], plo, rc[0], left > 0);
    ldrow(buf[1], pa[1], plo, rc[1], left > 1);
  }

  if (left > 0) {
    float acc[8];
#pragma unroll
    for (int c = 0; c < 8; ++c) acc[c] = 0.f;
    const uint32_t lutneg = (0x10000u - kLutLo) * 0x10001u + zero;
    int rem = min(pend, te) - s;
    uint32_t a2[4] = {0, 0, 0, 0};
    uint32_t bad = 0;
    int sst = s, tries = 0;
    while (true) {
    top:
      {
        const uint2 ra = lds64(rp + 8), rb = lds64(rp + 16);
        rc[2] = ra.x;
        rc[3] = ra.y;
        rc[4] = rb.x;
        rc[5] = rb.y;
      }
#pragma unroll
      for (int u = 0; u < 4; ++u) {
        if (__any_sync(0xffffffffu, rem == u)) {
          {
            if (u > 0) {
#pragma unroll
              for (int c = 0; c < 4; ++c) {
                acc[2 * c] += lo_f(a2[c]);
                acc[2 * c + 1] += hi_f(a2[c]);
                a2[c] = 0;
              }
            }
            if (__any_sync(0xffffffffu, ((bad & 1u) | mode | (uint32_t)(left == u)) != 0)) {
              if (__any_sync(0xffffffffu, bad & 1u)) {
                bad = 0;
                if (++tries < (1 << 16)) {
                  const int odd = sst & 1;
                  mode = (mode & 1u) | (odd << 1);
                  rp = sb + OFF_REC + (sst - odd) * 4;
                  left = te - sst + odd;
                  rem = odd ? 1 : min(pend, te) - sst;
                  rc[0] = lds32(rp);
                  rc[1] = lds32(rp + 4);
                  ldrow(buf[0], pa[0], plo, rc[0], true);
                  ldrow(buf[1], pa[1], plo, rc[1], left > 1);
#pragma unroll
                  for (int c = 0; c < 8; ++c) acc[c] = 0.f;
                  goto top;
                }
              }
              if (mode & 2u) {
                mode &= 1u;
                np -= 8;
                pend = sst;
              } else if (left == u) {
                goto done;
              } else if (mode) {
                store_side(sb, warp, lane, acc);
                mode = 0;
              } else {
                store_hsum(hl + (nx ^ l6), acc);
              }
            } else {
              store_hsum(hl + (nx ^ l6), acc);
            }
#pragma unroll
            for (int c = 0; c < 8; ++c) acc[c] = 0.f;
            sst = pend;
            do {
              np += 8;
              const uint2 e = lds64(np);
              pend = (int)e.x;
              nx = e.y;
            } while (pend == sst);
            rem = min(pend, te) - sst + u;
            q = lds128(sb + OFF_W1B + (ql ^ nx));
          }
        }
        const uint32_t v[4] = {buf[u & 1].x, buf[u & 1].y, buf[u & 1].z, buf[u & 1].w};
        asm volatile("lop3.b32 %0, %0, %1, %2, 0xf6;" : "+r"(bad) : "r"(v[0]), "r"(par));
        uint32_t y2[4];
        y2[0] = hadd2(hfma2_hi(rc[u], wp[0], v[0]), q.x);
        y2[1] = hadd2(hfma2_hi(rc[u], wp[1], v[1]), q.y);
        y2[2] = hadd2(hfma2_hi(rc[u], wp[2], v[2]), q.z);
        y2[3] = hadd2(hfma2_hi(rc[u], wp[3], v[3]), q.w);
        asm volatile("" ::: "memory");
        ldrow(buf[u & 1], pa[u & 1], plo, rc[u + 2], left > u + 2);
#pragma unroll
        for (int c = 0; c < 4; ++c) {
          uint32_t h;
          if (c == 0 || (c == 1 && u == 0)) {
            const uint32_t ab = y2[c] & 0x7fff7fffu;
            const uint32_t ix = __viaddmin_s16x2_relu(ab, lutneg, (kLutN - 1) * 0x10001u);
            uint32_t dl, dh;
            asm volatile("ld.shared.u8 %0, [%1];" : "=r"(dl) : "r"(sb + OFF_LUT + prmt(ix, 0, 0x4410)));
            asm volatile("ld.shared.u8 %0, [%1];" : "=r"(dh) : "r"(sb + OFF_LUT + prmt(ix, 0, 0x4432)));
            h = hfma2(ab, ix + kLutLo * 0x10001u - prmt(dl, dh, 0x5410), y2[c]);
          } else {
            h = hfma2(y2[c], htanh2(y2[c]), y2[c]);
          }
          a2[c] = u == 0 ? h : hadd2(a2[c], h);
        }
      }
#pragma unroll
      for (int c = 0; c < 4; ++c) {
        acc[2 * c] += lo_f(a2[c]);
        acc[2 * c + 1] += hi_f(a2[c]);
      }
#pragma unroll
      for (int u = 0; u < 2; ++u) rc[u] = rc[u + 4];
      rp += 16;
      left -= 4;
      rem -= 4;
    }
  done:
    if (mode) {
      store_side(sb, warp, lane, acc);
    } else {
      if (pend > te) {
        const int sl = (int)lds32(sb + OFF_RS + lane * 4), sn = (int)lds32(sb + OFF_RS + lane * 4 + 4);
        uint32_t mask = __ballot_sync(0xffffffffu, lane > warp && sl < pend && sl < sn);
        while (mask) {
          const int w2i = __ffs(mask) - 1;
          mask &= mask - 1;
#pragma unroll 1
          for (int it = 0; it < (1 << 22); ++it) {
            uint32_t rdy;
            asm volatile("ld.acquire.cta.shared.u32 %0, [%1];" : "=r"(rdy) : "r"(sb + OFF_RDY + w2i * 4) : "memory");
            if (rdy) break;
          }
          const uint4 u0 = lds128(sb + OFF_SIDE + w2i * 1024 + lane * 16), u1 = lds128(sb + OFF_SIDE + w2i * 1024 + 512 + lane * 16);
          acc[0] += __uint_as_float(u0.x); acc[1] += __uint_as_float(u0.y);
          acc[2] += __uint_as_float(u0.z); acc[3] += __uint_as_float(u0.w);
          acc[4] += __uint_as_float(u1.x); acc[5] += __uint_as_float(u1.y);
          acc[6] += __uint_as_float(u1.z); acc[7] += __uint_as_float(u1.w);
        }
      }
      store_hsum(hl + (nx ^ l6), acc);
    }
  }
  const uint32_t fm = lane < 5 ? lds32(sb + OFF_FLAG + lane * 4) : 0u;
  if (__any_sync(0xffffffffu, fm != 0)) {
    __syncthreads();
    for (int nd = warp; nd < nn; nd += kWarps) {
      const uint4 qv = lds128(sb + OFF_W1B + (ql ^ (nd * 128 + (nd & 7) * 16)));
      const uint32_t qq[4] = {qv.x, qv.y, qv.z, qv.w};
      float a[8];
      {
        const uint4 hv = lds128(hl + ((nd * 128 + (nd & 7) * 16) ^ l6));
        a[0] = lo_f(hv.x); a[1] = hi_f(hv.x); a[2] = lo_f(hv.y); a[3] = hi_f(hv.y);
        a[4] = lo_f(hv.z); a[5] = hi_f(hv.z); a[6] = lo_f(hv.w); a[7] = hi_f(hv.w);
      }
      int extra = 0;
      for (int p = 0; p < G; ++p) {
        if (!((__shfl_sync(0xffffffffu, fm, p >> 5) >> (p & 31)) & 1u)) continue;
        int no;
        asm volatile("ld.global.cg.s32 %0, [%1];" : "=r"(no) : "l"(g_ovf_cnt + p));
        for (int i0 = 0; i0 < no; i0 += 32) {
          uint2 en = make_uint2(0xffffffffu, 0);
          if (i0 + lane < no)
            asm volatile("ld.global.cg.v2.u32 {%0,%1}, [%2];" : "=r"(en.x), "=r"(en.y) : "l"(g_ovf + p * epc + i0 + lane));
          uint32_t mask = __ballot_sync(0xffffffffu, en.x == (uint32_t)(n0 + nd));
          extra += __popc(mask);
          while (mask) {
            const int j = __ffs(mask) - 1;
            mask &= mask - 1;
            const uint32_t r = __shfl_sync(0xffffffffu, en.y, j);
            uint4 pv = make_uint4(~par, 0, 0, 0);
#pragma unroll 1
            for (int it = 0; it < (1 << 20) && __any_sync(0xffffffffu, (pv.x ^ par) & 1u); ++it)
              ldrow(pv, pa[0], plo, r, true);
            const uint32_t v[4] = {pv.x, pv.y, pv.z, pv.w};
            const float ef = hi_f(r);
#pragma unroll
            for (int c = 0; c < 4; ++c) {
              const float ya = fmaf(ef, lo_f(wp[c]), lo_f(qq[c])) + lo_f(v[c]);
              const float yb = fmaf(ef, hi_f(wp[c]), hi_f(qq[c])) + hi_f(v[c]);
              a[2 * c] += fmaf(ya, ftanh(ya), ya);
              a[2 * c + 1] += fmaf(yb, ftanh(yb), yb);
            }
          }
        }
      }
      if (extra) {
        store_hsum(hl + ((nd * 128 + (nd & 7) * 16) ^ l6), a);
        if (lane == 0) sts32(sb + OFF_NCNT + nd * 4, lds32(sb + OFF_NCNT + nd * 4) + extra);
      }
    }
  }
  asm volatile("fence.proxy.async.shared::cta;" ::: "memory");
  if (wg >= 2) {
    bar_arrive(0, kThreads);
  } else {
    mbar_wait(barW2, 0);
    const uint32_t da = desc_lo(sb + OFF_W2 + wg * 32768), dh = desc_lo(sb + OFF_HS);
    bar_sync(0, kThreads);
    float o[40];
    wg_fence();
#pragma unroll
    for (int k = 0; k < 16; ++k)
      wgmma_n80(o, mk_desc(da + k * 128), mk_desc(dh + (k >> 2) * (kNT * 8) + (k & 3) * 2), k);
    wg_commit();
    const float bl = __uint_as_float((uint32_t)*reinterpret_cast<const uint16_t*>(sp + OFF_B2 + (64 * wg + 16 * wi + g) * 2) << 16);
    const float bh = __uint_as_float((uint32_t)*reinterpret_cast<const uint16_t*>(sp + OFF_B2 + (64 * wg + 16 * wi + g + 8) * 2) << 16);
    float cf[20];
#pragma unroll
    for (int j = 0; j < 10; ++j) {
      const int2 cc = *reinterpret_cast<const int2*>(sp + OFF_NCNT + (8 * j + 2 * t) * 4);
      cf[2 * j] = (float)cc.x;
      cf[2 * j + 1] = (float)cc.y;
    }
    const uint32_t stg = sb + OFF_W1B + wg * 16384;
    const uint32_t ad = stg + ((lane >> 4) * 8 + (lane & 7)) * 128 + (((2 * wi + ((lane >> 3) & 1)) ^ (lane & 7)) << 4);
    wg_wait();
#pragma unroll
    for (int j = 0; j < 10; j += 2) {
      uint32_t r[4];
#pragma unroll
      for (int jj = 0; jj < 2; ++jj) {
        const float c0 = cf[2 * (j + jj)], c1 = cf[2 * (j + jj) + 1];
        r[2 * jj] = pack2(fmaf(c0, bl, o[4 * (j + jj)]), fmaf(c1, bl, o[4 * (j + jj) + 1]));
        r[2 * jj + 1] = pack2(fmaf(c0, bh, o[4 * (j + jj) + 2]), fmaf(c1, bh, o[4 * (j + jj) + 3]));
      }
      stsm_t(ad + j * 1024, r[0], r[1], r[2], r[3]);
    }
    bar_sync(2 + wg, 128);
    {
      const int tw = tid & 127;
      uint4 ov[5];
#pragma unroll
      for (int i = 0; i < 5; ++i) {
        const int nd = (tw >> 3) + 16 * i;
        ov[i] = lds128(stg + nd * 128 + (((tw ^ nd) & 7) << 4));
      }
#pragma unroll
      for (int i = 0; i < 5; ++i) {
        const int nd = (tw >> 3) + 16 * i;
        if (nd < nn) *reinterpret_cast<uint4*>(out + (size_t)(n0 + nd) * 128 + wg * 64 + (tw & 7) * 8) = ov[i];
      }
    }
  }
}

__device__ __forceinline__ float bf2f(uint16_t v) { return __uint_as_float((uint32_t)v << 16); }
__global__ void fb_node(const uint16_t* x, const uint16_t* w1, const uint16_t* b1, int N) {
  float* P = reinterpret_cast<float*>(g_P);
  const int n = blockIdx.x, h = threadIdx.x;
  float p = 0.f, q = bf2f(b1[h]);
  for (int k = 0; k < 128; ++k) {
    const float xv = bf2f(x[(size_t)n * 128 + k]);
    p = fmaf(xv, bf2f(w1[k * 256 + h]), p);
    q = fmaf(xv, bf2f(w1[(128 + k) * 256 + h]), q);
  }
  P[(size_t)n * 256 + h] = p;
  P[(size_t)(N + n) * 256 + h] = q;
  P[(size_t)(2 * N + n) * 256 + h] = 0.f;
  if (h == 0) P[(size_t)3 * N * 256 + n] = 0.f;
}
__global__ void fb_edge(const uint16_t* ea, const int* src, const int* dst, const uint16_t* w1, int N) {
  float* P = reinterpret_cast<float*>(g_P);
  const int e = blockIdx.x, h = threadIdx.x, d = dst[e];
  const float v = P[(size_t)src[e] * 256 + h] + P[(size_t)(N + d) * 256 + h] + bf2f(ea[e]) * bf2f(w1[256 * 256 + h]);
  atomicAdd(&P[(size_t)(2 * N + d) * 256 + h], v / (1.f + __expf(-v)));
  if (h == 0) atomicAdd(&P[(size_t)3 * N * 256 + d], 1.f);
}
__global__ void fb_out(const uint16_t* w2, const uint16_t* b2, uint16_t* out, int N) {
  const float* P = reinterpret_cast<const float*>(g_P);
  const int n = blockIdx.x, c = threadIdx.x;
  float a = P[(size_t)3 * N * 256 + n] * bf2f(b2[c]);
  for (int k = 0; k < 256; ++k) a = fmaf(P[(size_t)(2 * N + n) * 256 + k], bf2f(w2[k * 128 + c]), a);
  out[(size_t)n * 128 + c] = (uint16_t)pack2(a, 0.f);
}

typedef CUresult (*EncodeFn)(CUtensorMap*, CUtensorMapDataType, cuuint32_t, void*, const cuuint64_t*, const cuuint64_t*,
                             const cuuint32_t*, const cuuint32_t*, CUtensorMapInterleave, CUtensorMapSwizzle,
                             CUtensorMapL2promotion, CUtensorMapFloatOOBfill);

void make_map(EncodeFn fn, CUtensorMap* m, const void* p, uint64_t cols, uint64_t rows, uint32_t box_rows) {
  cuuint64_t dims[2] = {cols, rows};
  cuuint64_t strides[1] = {cols * 2};
  cuuint32_t box[2] = {64, box_rows};
  cuuint32_t es[2] = {1, 1};
  fn(m, CU_TENSOR_MAP_DATA_TYPE_BFLOAT16, 2, const_cast<void*>(p), dims, strides, box, es,
     CU_TENSOR_MAP_INTERLEAVE_NONE, CU_TENSOR_MAP_SWIZZLE_128B, CU_TENSOR_MAP_L2_PROMOTION_L2_256B,
     CU_TENSOR_MAP_FLOAT_OOB_FILL_NONE);
}

}

extern "C" void kernel_launch(void* const* d_in, const int* in_sizes, int n_in, void* d_out, int out_size) {
  (void)n_in;
  (void)out_size;
  static EncodeFn enc = nullptr;
  static int grid = 0;
  if (!enc) {
    void* fp = nullptr;
    cudaDriverEntryPointQueryResult qr;
    cudaGetDriverEntryPoint("cuTensorMapEncodeTiled", &fp, cudaEnableDefault, &qr);
    enc = (EncodeFn)fp;
    cudaFuncSetAttribute(mpnn_kernel, cudaFuncAttributeMaxDynamicSharedMemorySize, kSmemBytes);
    int dev = 0, sms = 0;
    cudaGetDevice(&dev);
    cudaDeviceGetAttribute(&sms, cudaDevAttrMultiProcessorCount, dev);
    grid = sms < kMaxG ? sms : kMaxG;
  }
  const int N = in_sizes[0] / 128, E = in_sizes[2];
  const int npc = (N + grid - 1) / grid;
  if (npc < 64 || npc > kNT || (long long)N * npc > 15 * 65536 || E + 4 * grid > kMaxE) {
    if ((size_t)N * 769 * 4 > sizeof(g_P)) return;
    fb_node<<<N, 256, 0, cudaStreamPerThread>>>((const uint16_t*)d_in[0], (const uint16_t*)d_in[4], (const uint16_t*)d_in[5], N);
    fb_edge<<<E, 256, 0, cudaStreamPerThread>>>((const uint16_t*)d_in[1], (const int*)d_in[2], (const int*)d_in[3],
                                                (const uint16_t*)d_in[4], N);
    fb_out<<<N, 128, 0, cudaStreamPerThread>>>((const uint16_t*)d_in[6], (const uint16_t*)d_in[7], (uint16_t*)d_out, N);
    return;
  }
  const uint32_t magic = (uint32_t)(((1ull << 32) + npc - 1) / npc);
  const int epc = ((E + grid - 1) / grid + 3) & ~3;
  CUtensorMap tmX, tmW2, tmP, tmM, tmMi, tmWB;
  {
    void* pp = nullptr;
    cudaGetSymbolAddress(&pp, g_mbox);
    cuuint64_t dims[3] = {kCellB / 4, (cuuint64_t)kMaxG, (cuuint64_t)kMaxG};
    cuuint64_t strides[2] = {kCellB, (cuuint64_t)kCellB * kMaxG};
    cuuint32_t box[3] = {kCellB / 4, 1, (cuuint32_t)grid};
    cuuint32_t es[3] = {1, 1, 1};
    enc(&tmM, CU_TENSOR_MAP_DATA_TYPE_UINT32, 3, pp, dims, strides, box, es, CU_TENSOR_MAP_INTERLEAVE_NONE,
        CU_TENSOR_MAP_SWIZZLE_128B, CU_TENSOR_MAP_L2_PROMOTION_NONE, CU_TENSOR_MAP_FLOAT_OOB_FILL_NONE);
    cuuint32_t boxi[3] = {kCellB / 4, (cuuint32_t)grid, 1};
    enc(&tmMi, CU_TENSOR_MAP_DATA_TYPE_UINT32, 3, pp, dims, strides, boxi, es, CU_TENSOR_MAP_INTERLEAVE_NONE,
        CU_TENSOR_MAP_SWIZZLE_128B, CU_TENSOR_MAP_L2_PROMOTION_NONE, CU_TENSOR_MAP_FLOAT_OOB_FILL_NONE);
  }
  {
    cuuint64_t dims[3] = {64, 257, 4};
    cuuint64_t strides[2] = {512, 128};
    cuuint32_t box[3] = {64, 128, 4};
    cuuint32_t es[3] = {1, 1, 1};
    enc(&tmWB, CU_TENSOR_MAP_DATA_TYPE_BFLOAT16, 3, d_in[4], dims, strides, box, es, CU_TENSOR_MAP_INTERLEAVE_NONE,
        CU_TENSOR_MAP_SWIZZLE_128B, CU_TENSOR_MAP_L2_PROMOTION_L2_256B, CU_TENSOR_MAP_FLOAT_OOB_FILL_NONE);
  }
  uint64_t pbase;
  {
    void* pp = nullptr;
    cudaGetSymbolAddress(&pp, g_P);
    pbase = ((uint64_t)pp + (1u << 24) - 1) & ~(uint64_t)((1u << 24) - 1);
    cuuint64_t dims[4] = {64, (cuuint64_t)N, 2, 2};
    cuuint64_t strides[3] = {256, 128, 1u << 24};
    cuuint32_t box[4] = {64, (cuuint32_t)npc, 2, 2};
    cuuint32_t es[4] = {1, 1, 1, 1};
    enc(&tmP, CU_TENSOR_MAP_DATA_TYPE_BFLOAT16, 4, (void*)pbase, dims, strides, box, es, CU_TENSOR_MAP_INTERLEAVE_NONE,
        CU_TENSOR_MAP_SWIZZLE_128B, CU_TENSOR_MAP_L2_PROMOTION_NONE, CU_TENSOR_MAP_FLOAT_OOB_FILL_NONE);
  }
  {
    cuuint64_t dims[3] = {64, (cuuint64_t)N, 2};
    cuuint64_t strides[2] = {256, 128};
    cuuint32_t box[3] = {64, kNT, 2};
    cuuint32_t es[3] = {1, 1, 1};
    enc(&tmX, CU_TENSOR_MAP_DATA_TYPE_BFLOAT16, 3, d_in[0], dims, strides, box, es, CU_TENSOR_MAP_INTERLEAVE_NONE,
        CU_TENSOR_MAP_SWIZZLE_128B, CU_TENSOR_MAP_L2_PROMOTION_L2_256B, CU_TENSOR_MAP_FLOAT_OOB_FILL_NONE);
  }
  make_map(enc, &tmW2, d_in[6], 128, 256, 256);

  mpnn_kernel<<<grid, kThreads, kSmemBytes, cudaStreamPerThread>>>(
      (const int*)d_in[3], (const int*)d_in[2], (const uint16_t*)d_in[1], E, epc, N, npc, magic,
      (const uint16_t*)d_in[4], (const uint16_t*)d_in[6], (const uint16_t*)d_in[5], (const uint16_t*)d_in[7], pbase, (uint16_t*)d_out, tmX,
      tmW2, tmP, tmM, tmMi, tmWB);
}
```
